```python
import torch

def _softmax(x, axis=-1):
    return torch.softmax(x, dim=axis)
def _gelu(x):
    return torch.nn.functional.gelu(x, approximate="tanh")
def _silu(x):
    return torch.nn.functional.silu(x)
def _sigmoid(x):
    return torch.sigmoid(x)
def _layernorm(x, axis=-1, eps=1e-5):
    m = x.mean(dim=axis, keepdim=True)
    v = x.var(dim=axis, keepdim=True, unbiased=False)
    return (x - m) / torch.sqrt(v + eps)
def _scatter_add(tgt, idx, src, axis=0):
    return tgt.clone().index_add_(axis, idx, src)
def _segment_sum(src, seg, n):
    out = torch.zeros((n,) + src.shape[1:], dtype=src.dtype)
    return out.index_add_(0, seg, src)
def _pad(x, pw):
    flat = tuple(v for pair in reversed(pw) for v in pair)
    return torch.nn.functional.pad(x, flat)

kernel_name = 'gated_mix__ssm_conv_s4d__glu_gated_reglu__prompt'

def setup_inputs():

    _w = (lambda a: (lambda t: t.to(torch.bfloat16) if t.is_floating_point() else t)(torch.as_tensor(a)))
    def _A_setup():
        Bsz, L, D, N = 1, 2048, 512, 128
        return {
            "u": _w((lambda *s: torch.randn(*s, dtype=torch.bfloat16) * 0.05)(Bsz, L, D)),
            "log_A_real": _w((lambda *s: torch.randn(*s, dtype=torch.bfloat16) * 3.2)(D, N) * 0.5),
            "A_imag": _w((lambda *s: torch.randn(*s, dtype=torch.bfloat16) * 0.05)(D, N) * 3.14),
            "C_real": _w((lambda *s: torch.randn(*s, dtype=torch.bfloat16) * 0.05)(D, N) / N ** 0.5),
            "C_imag": _w((lambda *s: torch.randn(*s, dtype=torch.bfloat16) * 0.1)(D, N) / N ** 0.5),
            "log_dt": _w((lambda *s: torch.randn(*s, dtype=torch.bfloat16) * 0.05)(D) * 0.5 - 4.0),
            "D_skip": _w((lambda *s: torch.randn(*s, dtype=torch.bfloat16) * 0.05)(D)),
        }
    _A_in = _A_setup()

    def _B_setup():
        B, S, D, F = 1, 2048, 512, 1792
        return {
            "x": _w((lambda *s: torch.randn(*s, dtype=torch.bfloat16) * 0.05)(B, S, D)),
            "W_gate": _w((lambda *s: torch.randn(*s, dtype=torch.bfloat16) * 0.8)(D, F) * (2.0 / D) ** 0.5),
            "W_up": _w((lambda *s: torch.randn(*s, dtype=torch.bfloat16) * 0.8)(D, F) * (2.0 / D) ** 0.5),
            "W_down": _w((lambda *s: torch.randn(*s, dtype=torch.bfloat16) * 0.8)(F, D) * (1.0 / F) ** 0.5),
        }
    _B_in = _B_setup()

    return {
        "A_u": _A_in["u"],
        "A_log_A_real": _A_in["log_A_real"],
        "A_A_imag": _A_in["A_imag"],
        "A_C_real": _A_in["C_real"],
        "A_C_imag": _A_in["C_imag"],
        "A_log_dt": _A_in["log_dt"],
        "A_D_skip": _A_in["D_skip"],
        "B_x": _B_in["x"],
        "B_W_gate": _B_in["W_gate"],
        "B_W_up": _B_in["W_up"],
        "B_W_down": _B_in["W_down"],
        "gate_w": _w((lambda *s: torch.randn(*s, dtype=torch.bfloat16) * 0.05)(512) * 16.0),
    }

def reference(A_u, A_log_A_real, A_A_imag, A_C_real, A_C_imag, A_log_dt, A_D_skip, B_x, B_W_gate, B_W_up, B_W_down, gate_w):
    def _A_ref(u, log_A_real, A_imag, C_real, C_imag, log_dt, D_skip):
        L = u.shape[1]
        dt = torch.exp(log_dt)
        A = -torch.exp(log_A_real) + 1j * A_imag
        C = (C_real + 1j * C_imag) * dt[:, None]
        pos = (lambda x, dt: x.to(dt))(torch.arange(L), log_dt.dtype)
        P = torch.exp((A * dt[:, None])[:, :, None] * pos[None, None, :])
        K = 2.0 * torch.einsum("dn,dnl->dl", C, P).real
        L2 = 2 * L
        u_t = (lambda x, *d: x.permute(*d))(u, 0, 2, 1)
        Kf = (lambda x, *a, **k: torch.fft.rfft(x.float(), *a, **k))(K, L2)
        Uf = (lambda x, *a, **k: torch.fft.rfft(x.float(), *a, **k))(u_t, L2)
        y = (lambda x, *a, **k: torch.fft.irfft(x, *a, **k).to(torch.bfloat16))(Uf * Kf[None, :, :], L2)[:, :, :L]
        y = (lambda x, *d: x.permute(*d))(y, 0, 2, 1)
        return y + u * D_skip[None, None, :]

    def _B_ref(x, W_gate, W_up, W_down):
        gate = torch.einsum("bsd,df->bsf", x, W_gate)
        up = torch.einsum("bsd,df->bsf", x, W_up)
        gate = gate * (lambda x, dt: x.to(dt))(gate > 0, gate.dtype)
        h = gate * up
        return torch.einsum("bsf,fd->bsd", h, W_down)

    x = A_u
    g = _sigmoid((x * gate_w).sum(-1, keepdims=True))
    a = _A_ref(x, A_log_A_real, A_A_imag, A_C_real, A_C_imag, A_log_dt, A_D_skip)
    b = _B_ref(x, B_W_gate, B_W_up, B_W_down)
    return g * a + (1 - g) * b
```

```cpp
#include <cuda_runtime.h>
#include <cuda_bf16.h>
#include <cuda.h>
#include <stdint.h>

#define CV 3
#define CVN(G) (64 - 8 * G)
#define OQ 4
#define OQS 0
#define CREG "144"
namespace {

constexpr int SM_X   = 0;
constexpr int SM_W   = 131072;
constexpr int SM_C   = 196608;
constexpr int U_CP   = 1184;
constexpr int U_CH   = 4 * U_CP;
constexpr int SM_U   = SM_C;
constexpr int SM_P   = SM_U + 4 * U_CH;
constexpr int K_CH   = 1344;
constexpr int SM_K   = SM_P + 8320;
constexpr int SM_GA  = SM_C;
constexpr int SM_OUT = SM_C + 16384;
constexpr int SM_BAR = SM_C + 32768;
constexpr int B_XF = SM_BAR, B_WF = B_XF + 64, B_WE = B_WF + 256, B_GF = B_WE + 256, B_GE = B_GF + 256;
constexpr int SM_OM  = SM_BAR + 1088;
constexpr int SM_TOTAL = SM_OM + 256;
static_assert(SM_K + 4 * K_CH <= SM_BAR, "conv region");
static_assert(SM_TOTAL <= 232448, "smem");

__device__ uint4    g_h[16 * 28 * 1024];
__device__ uint4    g_a[512 * 256];
__device__ uint32_t g_g[1024];
__device__ uint32_t g_hflag[16 * 32];
__device__ uint32_t g_aflag[8 * 32];
__device__ uint32_t g_epoch[128];
#define PT(i)
#define PTL(i)

template<int TA,int TB> __device__ __forceinline__ void wgmma_ss_128(float (&d)[64], uint64_t da, uint64_t db, int sc) {
  asm volatile("{\n.reg .pred p;\nsetp.ne.b32 p, %66, 0;\nwgmma.mma_async.sync.aligned.m64n128k16.f32.bf16.bf16 {%0,%1,%2,%3,%4,%5,%6,%7,%8,%9,%10,%11,%12,%13,%14,%15,%16,%17,%18,%19,%20,%21,%22,%23,%24,%25,%26,%27,%28,%29,%30,%31,%32,%33,%34,%35,%36,%37,%38,%39,%40,%41,%42,%43,%44,%45,%46,%47,%48,%49,%50,%51,%52,%53,%54,%55,%56,%57,%58,%59,%60,%61,%62,%63}, %64, %65, p, 1, 1, %67, %68;\n}\n"
   : "+f"(d[0]),"+f"(d[1]),"+f"(d[2]),"+f"(d[3]),"+f"(d[4]),"+f"(d[5]),"+f"(d[6]),"+f"(d[7]),"+f"(d[8]),"+f"(d[9]),"+f"(d[10]),"+f"(d[11]),"+f"(d[12]),"+f"(d[13]),"+f"(d[14]),"+f"(d[15]),"+f"(d[16]),"+f"(d[17]),"+f"(d[18]),"+f"(d[19]),"+f"(d[20]),"+f"(d[21]),"+f"(d[22]),"+f"(d[23]),"+f"(d[24]),"+f"(d[25]),"+f"(d[26]),"+f"(d[27]),"+f"(d[28]),"+f"(d[29]),"+f"(d[30]),"+f"(d[31]),"+f"(d[32]),"+f"(d[33]),"+f"(d[34]),"+f"(d[35]),"+f"(d[36]),"+f"(d[37]),"+f"(d[38]),"+f"(d[39]),"+f"(d[40]),"+f"(d[41]),"+f"(d[42]),"+f"(d[43]),"+f"(d[44]),"+f"(d[45]),"+f"(d[46]),"+f"(d[47]),"+f"(d[48]),"+f"(d[49]),"+f"(d[50]),"+f"(d[51]),"+f"(d[52]),"+f"(d[53]),"+f"(d[54]),"+f"(d[55]),"+f"(d[56]),"+f"(d[57]),"+f"(d[58]),"+f"(d[59]),"+f"(d[60]),"+f"(d[61]),"+f"(d[62]),"+f"(d[63])
   : "l"(da), "l"(db), "r"(sc), "n"(TA), "n"(TB));
}
template<int N> __device__ __forceinline__ void wgmma_rs(float (&d)[32], uint32_t a0, uint32_t a1, uint32_t a2, uint32_t a3, uint64_t db, int sc);
template<> __device__ __forceinline__ void wgmma_rs<8>(float (&d)[32], uint32_t a0, uint32_t a1, uint32_t a2, uint32_t a3, uint64_t db, int sc) {
  asm volatile("{\n.reg .pred p;\nsetp.ne.b32 p, %9, 0;\nwgmma.mma_async.sync.aligned.m64n8k16.f32.bf16.bf16 {%0,%1,%2,%3}, {%4,%5,%6,%7}, %8, p, 1, 1, 0;\n}\n"
   : "+f"(d[0]),"+f"(d[1]),"+f"(d[2]),"+f"(d[3])
   : "r"(a0), "r"(a1), "r"(a2), "r"(a3), "l"(db), "r"(sc));
}
template<> __device__ __forceinline__ void wgmma_rs<16>(float (&d)[32], uint32_t a0, uint32_t a1, uint32_t a2, uint32_t a3, uint64_t db, int sc) {
  asm volatile("{\n.reg .pred p;\nsetp.ne.b32 p, %13, 0;\nwgmma.mma_async.sync.aligned.m64n16k16.f32.bf16.bf16 {%0,%1,%2,%3,%4,%5,%6,%7}, {%8,%9,%10,%11}, %12, p, 1, 1, 0;\n}\n"
   : "+f"(d[0]),"+f"(d[1]),"+f"(d[2]),"+f"(d[3]),"+f"(d[4]),"+f"(d[5]),"+f"(d[6]),"+f"(d[7])
   : "r"(a0), "r"(a1), "r"(a2), "r"(a3), "l"(db), "r"(sc));
}
template<> __device__ __forceinline__ void wgmma_rs<24>(float (&d)[32], uint32_t a0, uint32_t a1, uint32_t a2, uint32_t a3, uint64_t db, int sc) {
  asm volatile("{\n.reg .pred p;\nsetp.ne.b32 p, %17, 0;\nwgmma.mma_async.sync.aligned.m64n24k16.f32.bf16.bf16 {%0,%1,%2,%3,%4,%5,%6,%7,%8,%9,%10,%11}, {%12,%13,%14,%15}, %16, p, 1, 1, 0;\n}\n"
   : "+f"(d[0]),"+f"(d[1]),"+f"(d[2]),"+f"(d[3]),"+f"(d[4]),"+f"(d[5]),"+f"(d[6]),"+f"(d[7]),"+f"(d[8]),"+f"(d[9]),"+f"(d[10]),"+f"(d[11])
   : "r"(a0), "r"(a1), "r"(a2), "r"(a3), "l"(db), "r"(sc));
}
template<> __device__ __forceinline__ void wgmma_rs<32>(float (&d)[32], uint32_t a0, uint32_t a1, uint32_t a2, uint32_t a3, uint64_t db, int sc) {
  asm volatile("{\n.reg .pred p;\nsetp.ne.b32 p, %21, 0;\nwgmma.mma_async.sync.aligned.m64n32k16.f32.bf16.bf16 {%0,%1,%2,%3,%4,%5,%6,%7,%8,%9,%10,%11,%12,%13,%14,%15}, {%16,%17,%18,%19}, %20, p, 1, 1, 0;\n}\n"
   : "+f"(d[0]),"+f"(d[1]),"+f"(d[2]),"+f"(d[3]),"+f"(d[4]),"+f"(d[5]),"+f"(d[6]),"+f"(d[7]),"+f"(d[8]),"+f"(d[9]),"+f"(d[10]),"+f"(d[11]),"+f"(d[12]),"+f"(d[13]),"+f"(d[14]),"+f"(d[15])
   : "r"(a0), "r"(a1), "r"(a2), "r"(a3), "l"(db), "r"(sc));
}
template<> __device__ __forceinline__ void wgmma_rs<40>(float (&d)[32], uint32_t a0, uint32_t a1, uint32_t a2, uint32_t a3, uint64_t db, int sc) {
  asm volatile("{\n.reg .pred p;\nsetp.ne.b32 p, %25, 0;\nwgmma.mma_async.sync.aligned.m64n40k16.f32.bf16.bf16 {%0,%1,%2,%3,%4,%5,%6,%7,%8,%9,%10,%11,%12,%13,%14,%15,%16,%17,%18,%19}, {%20,%21,%22,%23}, %24, p, 1, 1, 0;\n}\n"
   : "+f"(d[0]),"+f"(d[1]),"+f"(d[2]),"+f"(d[3]),"+f"(d[4]),"+f"(d[5]),"+f"(d[6]),"+f"(d[7]),"+f"(d[8]),"+f"(d[9]),"+f"(d[10]),"+f"(d[11]),"+f"(d[12]),"+f"(d[13]),"+f"(d[14]),"+f"(d[15]),"+f"(d[16]),"+f"(d[17]),"+f"(d[18]),"+f"(d[19])
   : "r"(a0), "r"(a1), "r"(a2), "r"(a3), "l"(db), "r"(sc));
}
template<> __device__ __forceinline__ void wgmma_rs<48>(float (&d)[32], uint32_t a0, uint32_t a1, uint32_t a2, uint32_t a3, uint64_t db, int sc) {
  asm volatile("{\n.reg .pred p;\nsetp.ne.b32 p, %29, 0;\nwgmma.mma_async.sync.aligned.m64n48k16.f32.bf16.bf16 {%0,%1,%2,%3,%4,%5,%6,%7,%8,%9,%10,%11,%12,%13,%14,%15,%16,%17,%18,%19,%20,%21,%22,%23}, {%24,%25,%26,%27}, %28, p, 1, 1, 0;\n}\n"
   : "+f"(d[0]),"+f"(d[1]),"+f"(d[2]),"+f"(d[3]),"+f"(d[4]),"+f"(d[5]),"+f"(d[6]),"+f"(d[7]),"+f"(d[8]),"+f"(d[9]),"+f"(d[10]),"+f"(d[11]),"+f"(d[12]),"+f"(d[13]),"+f"(d[14]),"+f"(d[15]),"+f"(d[16]),"+f"(d[17]),"+f"(d[18]),"+f"(d[19]),"+f"(d[20]),"+f"(d[21]),"+f"(d[22]),"+f"(d[23])
   : "r"(a0), "r"(a1), "r"(a2), "r"(a3), "l"(db), "r"(sc));
}
template<> __device__ __forceinline__ void wgmma_rs<56>(float (&d)[32], uint32_t a0, uint32_t a1, uint32_t a2, uint32_t a3, uint64_t db, int sc) {
  asm volatile("{\n.reg .pred p;\nsetp.ne.b32 p, %33, 0;\nwgmma.mma_async.sync.aligned.m64n56k16.f32.bf16.bf16 {%0,%1,%2,%3,%4,%5,%6,%7,%8,%9,%10,%11,%12,%13,%14,%15,%16,%17,%18,%19,%20,%21,%22,%23,%24,%25,%26,%27}, {%28,%29,%30,%31}, %32, p, 1, 1, 0;\n}\n"
   : "+f"(d[0]),"+f"(d[1]),"+f"(d[2]),"+f"(d[3]),"+f"(d[4]),"+f"(d[5]),"+f"(d[6]),"+f"(d[7]),"+f"(d[8]),"+f"(d[9]),"+f"(d[10]),"+f"(d[11]),"+f"(d[12]),"+f"(d[13]),"+f"(d[14]),"+f"(d[15]),"+f"(d[16]),"+f"(d[17]),"+f"(d[18]),"+f"(d[19]),"+f"(d[20]),"+f"(d[21]),"+f"(d[22]),"+f"(d[23]),"+f"(d[24]),"+f"(d[25]),"+f"(d[26]),"+f"(d[27])
   : "r"(a0), "r"(a1), "r"(a2), "r"(a3), "l"(db), "r"(sc));
}
template<> __device__ __forceinline__ void wgmma_rs<64>(float (&d)[32], uint32_t a0, uint32_t a1, uint32_t a2, uint32_t a3, uint64_t db, int sc) {
  asm volatile("{\n.reg .pred p;\nsetp.ne.b32 p, %37, 0;\nwgmma.mma_async.sync.aligned.m64n64k16.f32.bf16.bf16 {%0,%1,%2,%3,%4,%5,%6,%7,%8,%9,%10,%11,%12,%13,%14,%15,%16,%17,%18,%19,%20,%21,%22,%23,%24,%25,%26,%27,%28,%29,%30,%31}, {%32,%33,%34,%35}, %36, p, 1, 1, 0;\n}\n"
   : "+f"(d[0]),"+f"(d[1]),"+f"(d[2]),"+f"(d[3]),"+f"(d[4]),"+f"(d[5]),"+f"(d[6]),"+f"(d[7]),"+f"(d[8]),"+f"(d[9]),"+f"(d[10]),"+f"(d[11]),"+f"(d[12]),"+f"(d[13]),"+f"(d[14]),"+f"(d[15]),"+f"(d[16]),"+f"(d[17]),"+f"(d[18]),"+f"(d[19]),"+f"(d[20]),"+f"(d[21]),"+f"(d[22]),"+f"(d[23]),"+f"(d[24]),"+f"(d[25]),"+f"(d[26]),"+f"(d[27]),"+f"(d[28]),"+f"(d[29]),"+f"(d[30]),"+f"(d[31])
   : "r"(a0), "r"(a1), "r"(a2), "r"(a3), "l"(db), "r"(sc));
}

__device__ __forceinline__ void wg_fence()  { asm volatile("wgmma.fence.sync.aligned;" ::: "memory"); }
__device__ __forceinline__ void wg_commit() { asm volatile("wgmma.commit_group.sync.aligned;" ::: "memory"); }
template<int N> __device__ __forceinline__ void wg_wait() { asm volatile("wgmma.wait_group.sync.aligned %0;" :: "n"(N) : "memory"); }
template<int N> __device__ __forceinline__ void pin(float (&d)[N]) {
#pragma unroll
  for (int i = 0; i < N; i++) asm volatile("" : "+f"(d[i]) :: "memory");
}
__device__ __forceinline__ uint64_t mkdesc(uint32_t addr, uint32_t lbo, uint32_t sbo, int sw) {
  return (uint64_t)((addr >> 4) & 0x3FFF) | ((uint64_t)(lbo >> 4) << 16) | ((uint64_t)(sbo >> 4) << 32) | ((uint64_t)sw << 62);
}
__device__ __forceinline__ void mbar_init(uint32_t b, int c) { asm volatile("mbarrier.init.shared::cta.b64 [%0], %1;" :: "r"(b), "r"(c) : "memory"); }
__device__ __forceinline__ void mbar_expect(uint32_t b, int bytes) { asm volatile("mbarrier.arrive.expect_tx.shared::cta.b64 _, [%0], %1;" :: "r"(b), "r"(bytes) : "memory"); }
__device__ __forceinline__ void mbar_arrive(uint32_t b) { asm volatile("mbarrier.arrive.shared::cta.b64 _, [%0];" :: "r"(b) : "memory"); }
__device__ __forceinline__ bool mbar_try(uint32_t b) {
  uint32_t ok;
  asm volatile("{.reg .pred p; mbarrier.try_wait.parity.shared::cta.b64 p, [%1], 0; selp.b32 %0, 1, 0, p;}" : "=r"(ok) : "r"(b) : "memory");
  return ok;
}
__device__ __forceinline__ void mbar_wait(uint32_t b) {
  if (mbar_try(b)) return;
  uint32_t t0 = clock();
  while (!mbar_try(b)) { if ((uint32_t)clock() - t0 > (1u << 30)) __trap(); }
}
__device__ __forceinline__ void tma2d(uint32_t dst, const CUtensorMap* tm, int c0, int c1, uint32_t bar) {
  asm volatile("cp.async.bulk.tensor.2d.shared::cluster.global.mbarrier::complete_tx::bytes [%0], [%1, {%2, %3}], [%4];"
               :: "r"(dst), "l"(tm), "r"(c0), "r"(c1), "r"(bar) : "memory");
}
__device__ __forceinline__ void tma5d(uint32_t dst, const CUtensorMap* tm, int c0, int c4, uint32_t bar) {
  asm volatile("cp.async.bulk.tensor.5d.shared::cluster.global.mbarrier::complete_tx::bytes [%0], [%1, {%2, %3, %3, %3, %4}], [%5];"
               :: "r"(dst), "l"(tm), "r"(c0), "r"(0), "r"(c4), "r"(bar) : "memory");
}
__device__ __forceinline__ void bulk_load(uint32_t dst, const void* src, int bytes, uint32_t bar) {
  asm volatile("cp.async.bulk.shared::cluster.global.mbarrier::complete_tx::bytes [%0], [%1], %2, [%3];"
               :: "r"(dst), "l"(src), "r"(bytes), "r"(bar) : "memory");
}
__device__ __forceinline__ void l2_prefetch(const void* src, int bytes) {
  asm volatile("cp.async.bulk.prefetch.L2.global [%0], %1;" :: "l"(src), "r"(bytes) : "memory");
}
__device__ __forceinline__ void fence_async_smem() { asm volatile("fence.proxy.async.shared::cta;" ::: "memory"); }
__device__ __forceinline__ void fence_async_all()  { asm volatile("fence.proxy.async;" ::: "memory"); }
__device__ __forceinline__ void bar_sync(int id, int n)   { asm volatile("bar.sync %0, %1;" :: "r"(id), "r"(n) : "memory"); }
__device__ __forceinline__ void bar_arrive(int id, int n) { asm volatile("bar.arrive %0, %1;" :: "r"(id), "r"(n) : "memory"); }
__device__ __forceinline__ void red_release(uint32_t* p, uint32_t v) { asm volatile("red.release.gpu.global.add.u32 [%0], %1;" :: "l"(p), "r"(v) : "memory"); }
__device__ __forceinline__ uint32_t ld_acquire(const uint32_t* p) { uint32_t v; asm volatile("ld.acquire.gpu.global.u32 %0, [%1];" : "=r"(v) : "l"(p) : "memory"); return v; }
__device__ __forceinline__ uint32_t ld_cg32(const void* p) { uint32_t v; asm volatile("ld.global.cg.u32 %0, [%1];" : "=r"(v) : "l"(p) : "memory"); return v; }
__device__ __forceinline__ uint4 ld_cg128(const void* p) { uint4 v; asm volatile("ld.global.cg.v4.u32 {%0,%1,%2,%3}, [%4];" : "=r"(v.x), "=r"(v.y), "=r"(v.z), "=r"(v.w) : "l"(p) : "memory"); return v; }
__device__ __forceinline__ void flag_wait(const uint32_t* p, uint32_t target) {
  uint32_t t0 = clock();
  while ((int)(ld_acquire(p) - target) < 0) { if ((uint32_t)clock() - t0 > (1u << 30)) __trap(); }
}
__device__ __forceinline__ uint32_t lds32(uint32_t a) { uint32_t v; asm volatile("ld.shared.u32 %0, [%1];" : "=r"(v) : "r"(a) : "memory"); return v; }
__device__ __forceinline__ uint32_t lds16(uint32_t a) { uint16_t v; asm volatile("ld.shared.u16 %0, [%1];" : "=h"(v) : "r"(a) : "memory"); return v; }
__device__ __forceinline__ uint2 lds64(uint32_t a) { uint2 v; asm volatile("ld.shared.v2.u32 {%0,%1}, [%2];" : "=r"(v.x), "=r"(v.y) : "r"(a) : "memory"); return v; }
__device__ __forceinline__ uint4 lds128(uint32_t a) { uint4 v; asm volatile("ld.shared.v4.u32 {%0,%1,%2,%3}, [%4];" : "=r"(v.x), "=r"(v.y), "=r"(v.z), "=r"(v.w) : "r"(a) : "memory"); return v; }
__device__ __forceinline__ void sts16(uint32_t a, uint32_t v) { asm volatile("st.shared.u16 [%0], %1;" :: "r"(a), "h"((uint16_t)v) : "memory"); }
__device__ __forceinline__ void sts32(uint32_t a, uint32_t v) { asm volatile("st.shared.u32 [%0], %1;" :: "r"(a), "r"(v) : "memory"); }
__device__ __forceinline__ void sts64(uint32_t a, uint32_t x, uint32_t y) { asm volatile("st.shared.v2.u32 [%0], {%1,%2};" :: "r"(a), "r"(x), "r"(y) : "memory"); }
__device__ __forceinline__ void sts128(uint32_t a, uint32_t x, uint32_t y, uint32_t z, uint32_t w) { asm volatile("st.shared.v4.u32 [%0], {%1,%2,%3,%4};" :: "r"(a), "r"(x), "r"(y), "r"(z), "r"(w) : "memory"); }
__device__ __forceinline__ uint32_t pack2(float lo, float hi)      { uint32_t r; asm("cvt.rn.bf16x2.f32 %0, %1, %2;" : "=r"(r) : "f"(hi), "f"(lo)); return r; }
__device__ __forceinline__ uint32_t pack2relu(float lo, float hi)  { uint32_t r; asm("cvt.rn.relu.bf16x2.f32 %0, %1, %2;" : "=r"(r) : "f"(hi), "f"(lo)); return r; }
__device__ __forceinline__ uint32_t mul2(uint32_t a, uint32_t b) { uint32_t r; asm("mul.rn.bf16x2 %0, %1, %2;" : "=r"(r) : "r"(a), "r"(b)); return r; }
__device__ __forceinline__ uint32_t add2(uint32_t a, uint32_t b) { uint32_t r; asm("add.rn.bf16x2 %0, %1, %2;" : "=r"(r) : "r"(a), "r"(b)); return r; }
__device__ __forceinline__ uint32_t sub2(uint32_t a, uint32_t b) { uint32_t r; asm("sub.rn.bf16x2 %0, %1, %2;" : "=r"(r) : "r"(a), "r"(b)); return r; }
__device__ __forceinline__ float bflo(uint32_t v) { return __uint_as_float(v << 16); }
__device__ __forceinline__ float bfhi(uint32_t v) { return __uint_as_float(v & 0xFFFF0000u); }
__device__ __forceinline__ float bfround(float x) { return bflo(pack2(x, 0.f)); }
__device__ __forceinline__ void mma16816(float (&c)[4], uint32_t a0, uint32_t a1, uint32_t a2, uint32_t a3, uint32_t b0, uint32_t b1) {
  asm("mma.sync.aligned.m16n8k16.row.col.f32.bf16.bf16.f32 {%0,%1,%2,%3}, {%4,%5,%6,%7}, {%8,%9}, {%0,%1,%2,%3};"
      : "+f"(c[0]), "+f"(c[1]), "+f"(c[2]), "+f"(c[3]) : "r"(a0), "r"(a1), "r"(a2), "r"(a3), "r"(b0), "r"(b1));
}
__device__ __forceinline__ float2 cexp_p(float al, float om, float p) {
  float mag; asm("ex2.approx.ftz.f32 %0, %1;" : "=f"(mag) : "f"(al * p));
  float t = __fadd_rn(fmaf(om, p, 12582912.f), -12582912.f);
  float r = fmaf(om, p, -t) * 6.283185307179586f;
  return make_float2(mag * __cosf(r), mag * __sinf(r));
}
__device__ __forceinline__ float2 cmul(float2 a, float2 b) {
  return make_float2(fmaf(a.x, b.x, -a.y * b.y), fmaf(a.x, b.y, a.y * b.x));
}

struct Params {
  const __nv_bfloat16 *u, *lar, *aim, *cre, *cim, *ldt, *dskip, *wg, *wu, *wd, *gw;
};

__device__ __forceinline__ void store_h(float (&acc)[64], uint4* tile, int row, int g, int q) {
#pragma unroll
  for (int rh = 0; rh < 2; rh++) {
#pragma unroll
    for (int jh = 0; jh < 2; jh++) {
      uint32_t v[4];
#pragma unroll
      for (int jl = 0; jl < 4; jl++) {
        const int j = 4 * jh + jl;
        v[jl] = mul2(pack2relu(acc[4 * j + 2 * rh], acc[4 * j + 2 * rh + 1]), pack2(acc[32 + 4 * j + 2 * rh], acc[32 + 4 * j + 2 * rh + 1]));
      }
      tile[(row + 8 * rh) * 8 + ((4 * jh + q) ^ g)] = make_uint4(v[0], v[1], v[2], v[3]);
    }
  }
}

template<int N> __device__ __forceinline__ void opq(float (&d)[32], uint32_t z) {
#pragma unroll
  for (int i = OQS; i < N; i++) asm volatile("xor.b32 %0, %0, %1;" : "+r"(*(uint32_t*)&d[i]) : "r"(z) : "memory");
}
template<int G> __device__ __forceinline__ void conv_load(uint32_t (&A)[32], uint32_t pa) {
#pragma unroll
  for (int jj = 0; jj < 4; jj++)
#pragma unroll
    for (int ks = 0; ks < 2; ks++) {
      const uint32_t a = pa - (4 * G + jj) * 256 + ks * 64;
      uint2 v0 = lds64(a), v1 = lds64(a + 8);
      A[8 * jj + 4 * ks] = v0.x; A[8 * jj + 4 * ks + 1] = v0.y; A[8 * jj + 4 * ks + 2] = v1.x; A[8 * jj + 4 * ks + 3] = v1.y;
    }
}
template<int G> __device__ __forceinline__ void conv_mma(float (&acc)[32], uint32_t (&A)[32], uint64_t db) {
  wg_fence();
#pragma unroll
  for (int jj = 0; jj < 4; jj++)
#pragma unroll
    for (int ks = 0; ks < 2; ks++)
      wgmma_rs<CVN(G)>(acc, A[8 * jj + 4 * ks], A[8 * jj + 4 * ks + 1], A[8 * jj + 4 * ks + 2], A[8 * jj + 4 * ks + 3],
                           db + (uint64_t)(2 * (4 * G + jj) + ks * (2 * U_CP / 16)), (G | jj | ks) != 0);
  wg_commit();
}

__global__ void __launch_bounds__(512, 1)
fused_kernel(const __grid_constant__ CUtensorMap tmX, const __grid_constant__ CUtensorMap tmG, const __grid_constant__ CUtensorMap tmU,
             const __grid_constant__ CUtensorMap tmD, const __grid_constant__ CUtensorMap tmO, const Params p) {
  extern __shared__ __align__(1024) uint8_t smem_raw[];
  const uint32_t sb = (uint32_t)__cvta_generic_to_shared(smem_raw);
  const int cta = blockIdx.x, m = cta >> 3, f = cta & 7;
  const int wgi = threadIdx.x >> 7, tid = threadIdx.x & 127, w = tid >> 5, lane = tid & 31, g = lane >> 2, q = lane & 3;
  const int ubase = 7 * (f >> 1) + 3 * (f & 1), ushared = 7 * (f >> 1) + 6;
  PT(wgi);

  if (wgi == 3) {
    if (sb & 1023) __trap();
    if (w < 2) {
      if ((lane & 1) == w) mbar_init(sb + B_WF + 8 * lane, 1);
      mbar_init(sb + (w ? B_GE : B_WE) + 8 * lane, 4);
    } else {
      if (lane < 8 && (lane & 1) == (w & 1)) mbar_init(sb + B_XF + 8 * lane, 1);
      if (w == 2) mbar_init(sb + B_GF + 8 * lane, 1);
    }
    asm volatile("fence.mbarrier_init.release.cluster;" ::: "memory");
    fence_async_smem();
    __syncwarp();
    if (lane == 0) {
      if (w < 2) {
        for (int s = w; s < 4; s += 2) {
          mbar_expect(sb + B_WF + 8 * s, 16384);
          tma2d(sb + SM_W + s * 16384, &tmG, ubase * 64, s * 64, sb + B_WF + 8 * s);
          tma2d(sb + SM_W + s * 16384 + 8192, &tmU, ubase * 64, s * 64, sb + B_WF + 8 * s);
        }
      } else {
        for (int k = w & 1; k < 8; k += 2) {
          mbar_expect(sb + B_XF + 8 * k, 16384);
          tma2d(sb + SM_X + k * 8192, &tmX, k * 64, m * 128, sb + B_XF + 8 * k);
          tma2d(sb + SM_X + 65536 + k * 8192, &tmX, k * 64, m * 128 + 64, sb + B_XF + 8 * k);
        }
      }
    }
  }
  __syncthreads();

  if (wgi < 2) {
    asm volatile("setmaxnreg.inc.sync.aligned.u32 168;");
    uint32_t epoch = 0;
    if (wgi == 1) {
      epoch = ld_cg32(&g_epoch[cta]);
      const int r = 16 * f + (tid >> 3), kb = tid & 7;
      uint4 gw[8];
#pragma unroll
      for (int c = 0; c < 8; c++) gw[c] = __ldg((const uint4*)(p.gw + 64 * kb + 8 * ((c + kb) & 7)));
#pragma unroll 1
      for (int k = 0; k < 8; k++) mbar_wait(sb + B_XF + 8 * k);
      const uint32_t rowa = sb + SM_X + (r >> 6) * 65536 + kb * 8192 + (r & 63) * 128;
      float s = 0.f;
#pragma unroll
      for (int c = 0; c < 8; c++) {
        uint4 xv = lds128(rowa + ((((c + kb) & 7) ^ (r & 7)) << 4));
        uint32_t p0 = mul2(xv.x, gw[c].x), p1 = mul2(xv.y, gw[c].y), p2 = mul2(xv.z, gw[c].z), p3 = mul2(xv.w, gw[c].w);
        s += ((bflo(p0) + bfhi(p0)) + (bflo(p1) + bfhi(p1))) + ((bflo(p2) + bfhi(p2)) + (bflo(p3) + bfhi(p3)));
      }
      s += __shfl_xor_sync(~0u, s, 1); s += __shfl_xor_sync(~0u, s, 2); s += __shfl_xor_sync(~0u, s, 4);
      s = bfround(s);
      const float gv = 1.f / (1.f + expf(-s));
      const float gn = __shfl_down_sync(~0u, gv, 8);
      if ((lane & 15) == 0) g_g[(m * 128 + r) >> 1] = pack2(gv, gn);
      __syncwarp();
      if (lane == 0) red_release(&g_hflag[m * 32 + 28], 1);
    }
    const uint64_t dX0 = mkdesc(sb + SM_X, 16, 1024, 1), dX1 = mkdesc(sb + SM_X + 65536, 16, 1024, 1);
    const uint64_t dW = mkdesc(sb + SM_W, 8192, 1024, 1);
    float acc0[64], acc1[64];
#pragma unroll 1
    for (int ui = wgi; ui < 3; ui += 2) {
#pragma unroll 1
      for (int k = 0; k < 8; k++) {
        const int s = ui * 8 + k;
        if (ui == 0) mbar_wait(sb + B_XF + 8 * k);
        mbar_wait(sb + B_WF + 8 * s);
        if (k == 0) PT(4 + ui);
        wg_fence();
#pragma unroll
        for (int kk = 0; kk < 4; kk++) {
          wgmma_ss_128<0, 1>(acc0, dX0 + k * 512 + kk * 2, dW + (k & 3) * 1024 + kk * 128, (k | kk) != 0);
          wgmma_ss_128<0, 1>(acc1, dX1 + k * 512 + kk * 2, dW + (k & 3) * 1024 + kk * 128, (k | kk) != 0);
        }
        wg_commit();
        wg_wait<1>();
        if (k > 0 && lane == 0) mbar_arrive(sb + B_WE + 8 * (s - 1));
      }
      wg_wait<0>();
      pin(acc0); pin(acc1);
      if (lane == 0) mbar_arrive(sb + B_WE + 8 * (ui * 8 + 7));
      PT(8 + ui);
      uint4* tile = g_h + (m * 28 + ubase + ui) * 1024;
      store_h(acc0, tile, 16 * w + g, g, q);
      store_h(acc1, tile, 64 + 16 * w + g, g, q);
      __syncwarp();
      if (lane == 0) red_release(&g_hflag[m * 32 + ubase + ui], 2);
      PT(12 + ui);
    }
    if (wgi == 1) {
      const uint64_t dXh = (f & 1) ? dX1 : dX0;
#pragma unroll 1
      for (int k = 0; k < 8; k++) {
        const int s = 24 + k;
        mbar_wait(sb + B_WF + 8 * s);
        if (k == 0) PT(7);
        wg_fence();
#pragma unroll
        for (int kk = 0; kk < 4; kk++)
          wgmma_ss_128<0, 1>(acc0, dXh + k * 512 + kk * 2, dW + (k & 3) * 1024 + kk * 128, (k | kk) != 0);
        wg_commit();
        wg_wait<1>();
        if (k > 0 && lane == 0) mbar_arrive(sb + B_WE + 8 * (s - 1));
      }
      wg_wait<0>();
      pin(acc0);
      if (lane == 0) mbar_arrive(sb + B_WE + 8 * 31);
      PT(11);
      store_h(acc0, g_h + (m * 28 + ushared) * 1024, (f & 1) * 64 + 16 * w + g, g, q);
      __syncwarp();
      if (lane == 0) red_release(&g_hflag[m * 32 + ushared], 1);
      PT(15);
      flag_wait(&g_hflag[m * 32 + 28], 32 * (epoch + 1));
      uint32_t gp[16];
#pragma unroll
      for (int i = 0; i < 16; i++) gp[i] = ld_cg32(&g_g[m * 64 + 4 * i + q]);
      if (tid < 4) {
#pragma unroll
        for (int i4 = 0; i4 < 4; i4++)
          sts128(sb + SM_OM + q * 64 + i4 * 16, sub2(0x3F803F80u, gp[4 * i4]), sub2(0x3F803F80u, gp[4 * i4 + 1]),
                 sub2(0x3F803F80u, gp[4 * i4 + 2]), sub2(0x3F803F80u, gp[4 * i4 + 3]));
      }
      flag_wait(&g_aflag[f * 32], 64 * (epoch + 1));
      PT(16);
      uint4 av[8];
#pragma unroll
      for (int c = 0; c < 8; c++) av[c] = ld_cg128(&g_a[(64 * f + 16 * w + g + 8 * (c >> 2)) * 256 + 16 * m + 4 * (c & 3) + q]);
      bar_sync(1, 256);
#pragma unroll
      for (int c = 0; c < 8; c++) {
        const int i0 = 4 * (c & 3);
        sts128(sb + SM_GA + c * 2048 + tid * 16, mul2(av[c].x, gp[i0]), mul2(av[c].y, gp[i0 + 1]), mul2(av[c].z, gp[i0 + 2]), mul2(av[c].w, gp[i0 + 3]));
      }
      bar_arrive(2, 256);
      PT(17);
    } else {
      const uint32_t xd = sb + SM_X + ((f & 1) ^ 1) * 65536, xl = sb + SM_X + (f & 1) * 65536;
#pragma unroll 1
      for (int i = 0; i < 28; i++) {
        const int sl = i & 7;
        const uint32_t ha = sl < 3 ? xd + sl * 24576 : (sl == 3 ? xl + 8192 : sb + SM_W + (sl - 4) * 16384);
        const uint32_t wa = sl < 2 ? xd + sl * 24576 + 16384 : (sl == 2 ? xl : xl + sl * 8192);
        const uint64_t dA = mkdesc(wa, 16, 1024, 1), dB = mkdesc(ha, 16, 1024, 1);
        mbar_wait(sb + B_GF + 8 * i);
        PT(20 + i);
        wg_fence();
#pragma unroll
        for (int kk = 0; kk < 4; kk++) wgmma_ss_128<1, 0>(acc0, dA + kk * 128, dB + kk * 2, (i | kk) != 0);
        wg_commit();
        wg_wait<1>();
        if (i > 0 && lane == 0) mbar_arrive(sb + B_GE + 8 * (i - 1));
      }
      bar_sync(2, 256);
      uint4 ga[8], om[4];
#pragma unroll
      for (int c = 0; c < 8; c++) ga[c] = lds128(sb + SM_GA + c * 2048 + tid * 16);
#pragma unroll
      for (int c = 0; c < 4; c++) om[c] = lds128(sb + SM_OM + q * 64 + c * 16);
      wg_wait<0>();
      pin(acc0);
      PT(18);
      const uint32_t oa = sb + SM_OUT + ((lane >> 4) * 8 + (lane & 7)) * 128 + (((2 * w + ((lane >> 3) & 1)) ^ (lane & 7)) << 4);
#pragma unroll
      for (int i2 = 0; i2 < 8; i2++) {
        uint32_t r[4];
#pragma unroll
        for (int e = 0; e < 2; e++) {
          const int i = 2 * i2 + e;
          const uint32_t o = ((const uint32_t*)om)[i];
          r[2 * e]     = add2(((const uint32_t*)ga)[i],      mul2(o, pack2(acc0[4 * i], acc0[4 * i + 1])));
          r[2 * e + 1] = add2(((const uint32_t*)ga)[16 + i], mul2(o, pack2(acc0[4 * i + 2], acc0[4 * i + 3])));
        }
        asm volatile("stmatrix.sync.aligned.m8n8.x4.trans.shared.b16 [%0], {%1,%2,%3,%4};"
                     :: "r"(oa + i2 * 2048), "r"(r[0]), "r"(r[1]), "r"(r[2]), "r"(r[3]) : "memory");
      }
      fence_async_smem();
      bar_sync(3, 128);
      if (tid == 0) {
        asm volatile("cp.async.bulk.tensor.2d.global.shared::cta.bulk_group [%0, {%1, %2}], [%3];"
                     :: "l"(&tmO), "r"(f * 64), "r"(m * 128), "r"(sb + SM_OUT) : "memory");
        asm volatile("cp.async.bulk.commit_group;" ::: "memory");
        atomicAdd(&g_epoch[cta], 1u);
        asm volatile("cp.async.bulk.wait_group.read 0;" ::: "memory");
      }
      PT(19);
    }
  } else if (wgi == 2) {
    asm volatile("setmaxnreg.inc.sync.aligned.u32 " CREG ";");
    const int d = 4 * cta + w;
    const uint2 r_lar = __ldg((const uint2*)(p.lar + d * 128) + lane), r_aim = __ldg((const uint2*)(p.aim + d * 128) + lane);
    const uint2 r_cre = __ldg((const uint2*)(p.cre + d * 128) + lane), r_cim = __ldg((const uint2*)(p.cim + d * 128) + lane);
    const float ldt = __bfloat162float(p.ldt[d]);
    const uint2 dsk = __ldg((const uint2*)(p.dskip) + cta);
    {
      uint2 ur[16];
#pragma unroll
      for (int i = 0; i < 16; i++) ur[i] = __ldg((const uint2*)(p.u + (tid * 16 + i) * 512) + cta);
      sts128(sb + SM_U + (tid >> 3) * U_CP + (64 + (tid & 7)) * 16, 0, 0, 0, 0);
      const float dt = bfround(expf(ldt));
#pragma unroll
      for (int i = 0; i < 4; i++) {
        const uint32_t a = i < 2 ? r_lar.x : r_lar.y, b = i < 2 ? r_aim.x : r_aim.y, c = i < 2 ? r_cre.x : r_cre.y, e = i < 2 ? r_cim.x : r_cim.y;
        const float ar = bfround(expf((i & 1) ? bfhi(a) : bflo(a)));
        const float al = -(ar * dt) * 1.4426950408889634f;
        const float om = (((i & 1) ? bfhi(b) : bflo(b)) * dt) * 0.15915494309189535f;
        const float cr = 2.f * (((i & 1) ? bfhi(c) : bflo(c)) * dt), ci = 2.f * (((i & 1) ? bfhi(e) : bflo(e)) * dt);
        const float2 z = cexp_p(al, om, 64.f);
        sts128(sb + SM_P + w * 2048 + (4 * lane + i) * 16, __float_as_uint(al), __float_as_uint(om), __float_as_uint(cr), __float_as_uint(ci));
        sts64(sb + SM_K + w * K_CH + (4 * lane + i) * 8, __float_as_uint(z.x), __float_as_uint(z.y));
      }
      PT(48);
      const uint32_t ua = sb + SM_U + (tid & 1) * 2 * U_CP + (63 - (tid >> 1)) * 16;
#pragma unroll
      for (int c = 0; c < 4; c++)
#pragma unroll
        for (int cc = 0; cc < 2; cc++) {
          uint32_t v[4];
#pragma unroll
          for (int qq = 0; qq < 4; qq++) {
            const uint2 x0 = ur[4 * qq + 2 * cc], x1 = ur[4 * qq + 2 * cc + 1];
            v[qq] = __byte_perm(c < 2 ? x0.x : x0.y, c < 2 ? x1.x : x1.y, (c & 1) ? 0x7632 : 0x5410);
          }
          sts128(ua + c * U_CH + cc * U_CP, v[0], v[1], v[2], v[3]);
        }
      fence_async_smem();
    }
    __syncwarp();
    PT(49);
    {
      float kc[2][3][4];
#pragma unroll
      for (int i = 0; i < 24; i++) ((float*)kc)[i] = 0.f;
      const float p0 = 8.f * g, b0 = g, b1 = g < 4 ? 256.f + 2.f * g : 256.f * (g >> 1) + 4.f * (g & 1), b2 = 1024.f + 256.f * g;
#pragma unroll 2
      for (int s = 0; s < 16; s++) {
        uint32_t A[2][4], B[2][3];
#pragma unroll
        for (int h = 0; h < 2; h++) {
          const int n = 8 * s + 4 * h + q;
          const uint4 pr = lds128(sb + SM_P + w * 2048 + n * 16);
          const uint2 zr = lds64(sb + SM_K + w * K_CH + n * 8);
          const float al = __uint_as_float(pr.x), om = __uint_as_float(pr.y);
          const float2 c = make_float2(__uint_as_float(pr.z), __uint_as_float(pr.w)), z = make_float2(__uint_as_float(zr.x), __uint_as_float(zr.y));
          float2 v = cexp_p(al, om, p0);
          A[h][0] = pack2(v.x, v.y); v = cmul(v, z);
          A[h][1] = pack2(v.x, v.y); v = cmul(v, z);
          A[h][2] = pack2(v.x, v.y); v = cmul(v, z);
          A[h][3] = pack2(v.x, v.y);
          v = cmul(c, cexp_p(al, om, b0)); B[h][0] = pack2(v.x, -v.y);
          v = cmul(c, cexp_p(al, om, b1)); B[h][1] = pack2(v.x, -v.y);
          v = cmul(c, cexp_p(al, om, b2)); B[h][2] = pack2(v.x, -v.y);
        }
#pragma unroll
        for (int mt = 0; mt < 2; mt++)
#pragma unroll
          for (int nt = 0; nt < 3; nt++)
            mma16816(kc[mt][nt], A[0][2 * mt], A[0][2 * mt + 1], A[1][2 * mt], A[1][2 * mt + 1], B[0][nt], B[1][nt]);
      }
      __syncwarp();
      const uint32_t ka = sb + SM_K + w * K_CH;
#pragma unroll
      for (int mt = 0; mt < 2; mt++)
#pragma unroll
        for (int rh = 0; rh < 2; rh++) {
          const int row = 16 * mt + 8 * rh + g;
          sts32(ka + 2 * (8 * row + 2 * q), pack2(kc[mt][0][2 * rh], kc[mt][0][2 * rh + 1]));
          sts32(ka + 2 * (q < 2 ? 256 + 4 * row + 2 * q : 256 + 64 * q + 2 * row), pack2(kc[mt][1][2 * rh], kc[mt][1][2 * rh + 1]));
          const uint32_t v = pack2(kc[mt][2][2 * rh], kc[mt][2][2 * rh + 1]);
          if (q < 3) sts16(ka + 2 * (512 + 64 * q + row), v);
          if (q < 2) sts16(ka + 2 * (544 + 64 * q + row), v >> 16);
        }
    }
    PT(50);
#pragma unroll 1
    for (int c = 0; c < 4; c++) {
      bar_sync(4, 128);
      const uint32_t ka = sb + SM_K + c * K_CH;
#pragma unroll
      for (int it = 0; it < 4; it++) {
        const int x0 = 2047 - 4 * (tid + 128 * it);
        uint32_t kv[5];
#pragma unroll
        for (int e = 0; e < 5; e++) {
          const int l = x0 - e;
          const int idx = l < 128 ? l : (int)(pack2((float)l, 0.f)) - 0x4300 + 128;
          kv[e] = (it < 3 || l >= 0) ? lds16(ka + 2 * idx) : 0u;
        }
        sts128(sb + SM_P + (tid + 128 * it) * 16, kv[0] | (kv[1] << 16), kv[1] | (kv[2] << 16), kv[2] | (kv[3] << 16), kv[3] | (kv[4] << 16));
      }
      if (tid < 8) sts128(sb + SM_P + 8192 + tid * 16, 0, 0, 0, 0);
      bar_sync(4, 128);
      PT(51 + 3 * c);
      float acc[32];
      const uint32_t zero = lds32(sb + SM_P + 8192 + 64);
      uint32_t A0[32], A1[32];
      const uint32_t pa = sb + SM_P + 4 * (2046 - 16 * w - 2 * g + 4 * q);
      const uint64_t db = mkdesc(sb + SM_U + c * U_CH, U_CP, 128, 0);
      conv_load<0>(A0, pa);
      conv_mma<0>(acc, A0, db); conv_load<1>(A1, pa); wg_wait<0>(); opq<28+OQ>(acc, zero);
      conv_mma<1>(acc, A1, db); conv_load<2>(A0, pa); wg_wait<0>(); opq<24+OQ>(acc, zero);
      conv_mma<2>(acc, A0, db); conv_load<3>(A1, pa); wg_wait<0>(); opq<20+OQ>(acc, zero);
      conv_mma<3>(acc, A1, db); conv_load<4>(A0, pa); wg_wait<0>(); opq<16+OQ>(acc, zero);
      conv_mma<4>(acc, A0, db); conv_load<5>(A1, pa); wg_wait<0>(); opq<12+OQ>(acc, zero);
      conv_mma<5>(acc, A1, db); conv_load<6>(A0, pa); wg_wait<0>(); opq<8+OQ>(acc, zero);
      conv_mma<6>(acc, A0, db); conv_load<7>(A1, pa); wg_wait<0>(); opq<4+OQ>(acc, zero);
      conv_mma<7>(acc, A1, db);
      bar_sync(4, 128);
      wg_wait<0>();
      pin(acc);
      PT(52 + 3 * c);
      const int r0 = 16 * (w & 1) + 2 * g;
      if (w >= 2) {
#pragma unroll
        for (int i = 0; i < 8; i++)
#pragma unroll
          for (int e = 0; e < 2; e++) {
            const int a = 64 - (8 * i + 2 * q + e);
            const int sw = (((a >> 1) + 2 * (a & 1)) & 3) << 3;
            if (a < 64) sts64(sb + SM_P + 4 * (32 * a + (r0 ^ sw)), __float_as_uint(acc[4 * i + 2 + e]), __float_as_uint(acc[4 * i + e]));
          }
      }
      bar_sync(4, 128);
      if (w < 2) {
#pragma unroll
        for (int i = 0; i < 8; i++)
#pragma unroll
          for (int e = 0; e < 2; e++) {
            const int a = 63 - (8 * i + 2 * q + e);
            const int sw = (((a >> 1) + 2 * (a & 1)) & 3) << 3;
            const uint32_t ad = sb + SM_P + 4 * (32 * a + (r0 ^ sw));
            float y0 = acc[4 * i + 2 + e], y1 = acc[4 * i + e];
            if (a > 0) { const uint2 o = lds64(ad); y0 += __uint_as_float(o.x); y1 += __uint_as_float(o.y); }
            sts64(ad, __float_as_uint(y0), __float_as_uint(y1));
          }
      }
      bar_sync(4, 128);
      const uint32_t dw = (c & 2) ? dsk.y : dsk.x;
      const uint32_t dd = __byte_perm(dw, dw, (c & 1) ? 0x3232 : 0x1010);
#pragma unroll
      for (int hh = 0; hh < 2; hh++) {
        const int piece = tid + 128 * hh, a = piece >> 2;
        const int sw = (((a >> 1) + 2 * (a & 1)) & 3) << 3;
        uint32_t v[4];
#pragma unroll
        for (int il = 0; il < 4; il++) {
          const uint2 y = lds64(sb + SM_P + 4 * (32 * a + ((8 * il + 2 * q) ^ sw)));
          const uint32_t uu = lds32(sb + SM_U + c * U_CH + (2 * (il >> 1) + (q & 1)) * U_CP + (63 - a) * 16 + 4 * (2 * (il & 1) + (q >> 1)));
          v[il] = add2(pack2(__uint_as_float(y.x), __uint_as_float(y.y)), mul2(uu, dd));
        }
        g_a[(4 * cta + c) * 256 + piece] = make_uint4(v[0], v[1], v[2], v[3]);
      }
      PT(53 + 3 * c);
    }
    bar_arrive(1, 256);
    __syncwarp();
    if (lane == 0) red_release(&g_aflag[(cta >> 4) * 32], 1);
    PT(63);
  } else {
    asm volatile("setmaxnreg.dec.sync.aligned.u32 32;");
    if (w == 0) {
      if (lane == 0) {
#pragma unroll 1
        for (int s = 4; s < 32; s++) {
          const int col = (s < 24 ? ubase + (s >> 3) : ushared) * 64;
          mbar_wait(sb + B_WE + 8 * (s - 4));
          mbar_expect(sb + B_WF + 8 * s, 16384);
          tma2d(sb + SM_W + (s & 3) * 16384, &tmG, col, (s & 7) * 64, sb + B_WF + 8 * s);
          tma2d(sb + SM_W + (s & 3) * 16384 + 8192, &tmU, col, (s & 7) * 64, sb + B_WF + 8 * s);
        }
      }
    } else if (w == 1) {
      const uint32_t target = 8 * (ld_cg32(&g_epoch[cta]) + 1);
      const int unit = lane < 24 ? 7 * ((lane & 7) >> 1) + 3 * (lane & 1) + (lane >> 3) : 7 * (lane & 3) + 6;
      const int sl = lane & 7;
      const uint32_t xd = sb + SM_X + ((f & 1) ^ 1) * 65536, xl = sb + SM_X + (f & 1) * 65536;
      const uint32_t ha = sl < 3 ? xd + sl * 24576 : (sl == 3 ? xl + 8192 : sb + SM_W + (sl - 4) * 16384);
      const uint32_t wa = sl < 2 ? xd + sl * 24576 + 16384 : (sl == 2 ? xl : xl + sl * 8192);
      const uint32_t* fl = &g_hflag[m * 32 + unit];
      uint32_t ready = 0;
#pragma unroll 1
      for (int i = 0; i < 28; i++) {
        mbar_wait(i < 8 ? sb + B_WE + 8 * (i < 4 ? 18 + 3 * i : 24 + i) : sb + B_GE + 8 * (i - 8));
        if (lane == i) {
          mbar_expect(sb + B_GF + 8 * i, 24576);
          tma5d(wa, &tmD, f * 64, 2 * unit, sb + B_GF + 8 * i);
        }
        if (!((ready >> i) & 1)) {
          const uint32_t t0 = clock();
          do {
            ready = __ballot_sync(~0u, (int)(ld_acquire(fl) - target) >= 0);
            if ((uint32_t)clock() - t0 > (1u << 30)) __trap();
          } while (!((ready >> i) & 1));
          fence_async_all();
        }
        if (lane == i) bulk_load(ha, g_h + (m * 28 + unit) * 1024, 16384, sb + B_GF + 8 * i);
      }
    } else if (w == 2) {
      if (lane == 0) {
        l2_prefetch(p.wg + cta * 7168, 14336);
        l2_prefetch(p.wu + cta * 7168, 14336);
        l2_prefetch(p.wd + cta * 7168, 14336);
      }
    }
  }
}

typedef CUresult (*EncFn)(CUtensorMap*, CUtensorMapDataType, cuuint32_t, void*, const cuuint64_t*, const cuuint64_t*, const cuuint32_t*,
                          const cuuint32_t*, CUtensorMapInterleave, CUtensorMapSwizzle, CUtensorMapL2promotion, CUtensorMapFloatOOBfill);

void encode(EncFn fn, CUtensorMap* tm, void* base, int rank, const cuuint64_t* gd, const cuuint64_t* gs, const cuuint32_t* bd) {
  const cuuint32_t es[5] = {1, 1, 1, 1, 1};
  fn(tm, CU_TENSOR_MAP_DATA_TYPE_BFLOAT16, rank, base, gd, gs, bd, es, CU_TENSOR_MAP_INTERLEAVE_NONE, CU_TENSOR_MAP_SWIZZLE_128B,
     CU_TENSOR_MAP_L2_PROMOTION_L2_128B, CU_TENSOR_MAP_FLOAT_OOB_FILL_NONE);
}

}

extern "C" void kernel_launch(void* const* d_in, const int* in_sizes, int n_in, void* d_out, int out_size) {
  static EncFn fn = nullptr;
  if (!fn) {
    cudaDriverEntryPointQueryResult qr;
    cudaGetDriverEntryPoint("cuTensorMapEncodeTiled", (void**)&fn, cudaEnableDefault, &qr);
    cudaFuncSetAttribute(fused_kernel, cudaFuncAttributeMaxDynamicSharedMemorySize, SM_TOTAL);
  }
  CUtensorMap tmX, tmG, tmU, tmD, tmO;
  {
    const cuuint64_t gd[2] = {512, 2048}, gs[1] = {1024};
    const cuuint32_t bx[2] = {64, 64}, bo[2] = {64, 128};
    encode(fn, &tmX, d_in[0], 2, gd, gs, bx);
    encode(fn, &tmO, d_out, 2, gd, gs, bo);
  }
  {
    const cuuint64_t gd[2] = {1792, 512}, gs[1] = {3584};
    const cuuint32_t bd[2] = {64, 64};
    encode(fn, &tmG, d_in[8], 2, gd, gs, bd);
    encode(fn, &tmU, d_in[9], 2, gd, gs, bd);
  }
  {
    const cuuint64_t gd[5] = {512, 2, 4, 4, 56}, gs[4] = {1024, 8192, 2048, 32768};
    const cuuint32_t bd[5] = {64, 2, 4, 4, 2};
    encode(fn, &tmD, d_in[10], 5, gd, gs, bd);
  }
  Params p;
  p.u = (const __nv_bfloat16*)d_in[0];   p.lar = (const __nv_bfloat16*)d_in[1]; p.aim = (const __nv_bfloat16*)d_in[2];
  p.cre = (const __nv_bfloat16*)d_in[3]; p.cim = (const __nv_bfloat16*)d_in[4]; p.ldt = (const __nv_bfloat16*)d_in[5];
  p.dskip = (const __nv_bfloat16*)d_in[6]; p.wg = (const __nv_bfloat16*)d_in[8]; p.wu = (const __nv_bfloat16*)d_in[9];
  p.wd = (const __nv_bfloat16*)d_in[10]; p.gw = (const __nv_bfloat16*)d_in[11];
  fused_kernel<<<128, 512, SM_TOTAL, cudaStreamPerThread>>>(tmX, tmG, tmU, tmD, tmO, p);
}
```

```cpp
#include <cuda_runtime.h>
#include <cuda_bf16.h>
#include <cuda.h>
#include <stdint.h>

#define PFA 1
#define LAG 2
#define PMASK 0xFFFF
#define SS 1
#define RG 168
#define RC 144
#define RP 32
#define STR_(x) #x
#define STR(x) STR_(x)
namespace {

constexpr uint32_t SB    = 1024;
constexpr uint32_t SM_X  = SB;
constexpr uint32_t SM_W  = SM_X + 131072;
constexpr uint32_t SM_C  = SM_W + 65536;
constexpr uint32_t SM_KA = SM_C;
constexpr uint32_t SM_KB = SM_C + 16384;
constexpr uint32_t U_CP  = 2176;
constexpr uint32_t SM_U  = SM_C;
constexpr uint32_t SM_T  = SM_U + 8 * U_CP;
constexpr uint32_t K_CH  = 1344;
constexpr uint32_t SM_K  = SM_C + 28672;
constexpr uint32_t SM_GW = SM_K + 4 * K_CH;
constexpr uint32_t SM_OUT = SM_W + 32768;
constexpr uint32_t B_WE = SM_GW + 1024, B_GE = B_WE + 32, B_XF = B_GE + 64, B_WF = B_XF + 64, B_GF = B_WF + 32, B_HR = B_GF + 64, B_UF = B_HR + 48;
constexpr uint32_t SM_PROF = B_UF + 16;
constexpr uint32_t SM_TOTAL = SM_PROF + 448 - SB;
static_assert(SM_TOTAL <= 232448, "smem");

constexpr int TPM = 37;
__device__ uint4    g_t[16 * TPM * 1024];
__device__ uint4    g_ut[512 * 272];
__device__ uint32_t g_flag[96 * 32];
#define PT(G, i)
#define PG(i)

template<int TA,int TB> __device__ __forceinline__ void wgmma_ss_128(float (&d)[64], uint32_t alo, uint32_t ahi, uint32_t blo, uint32_t bhi, int sc) {
  asm volatile("{\n.reg .pred p;\n.reg .b64 da, db;\nmov.b64 da, {%64, %65};\nmov.b64 db, {%66, %67};\nsetp.ne.b32 p, %68, 0;\n"
   "wgmma.mma_async.sync.aligned.m64n128k16.f32.bf16.bf16 {%0,%1,%2,%3,%4,%5,%6,%7,%8,%9,%10,%11,%12,%13,%14,%15,%16,%17,%18,%19,%20,%21,%22,%23,%24,%25,%26,%27,%28,%29,%30,%31,%32,%33,%34,%35,%36,%37,%38,%39,%40,%41,%42,%43,%44,%45,%46,%47,%48,%49,%50,%51,%52,%53,%54,%55,%56,%57,%58,%59,%60,%61,%62,%63}, da, db, p, 1, 1, %69, %70;\n}\n"
   : "+f"(d[0]),"+f"(d[1]),"+f"(d[2]),"+f"(d[3]),"+f"(d[4]),"+f"(d[5]),"+f"(d[6]),"+f"(d[7]),"+f"(d[8]),"+f"(d[9]),"+f"(d[10]),"+f"(d[11]),"+f"(d[12]),"+f"(d[13]),"+f"(d[14]),"+f"(d[15]),"+f"(d[16]),"+f"(d[17]),"+f"(d[18]),"+f"(d[19]),"+f"(d[20]),"+f"(d[21]),"+f"(d[22]),"+f"(d[23]),"+f"(d[24]),"+f"(d[25]),"+f"(d[26]),"+f"(d[27]),"+f"(d[28]),"+f"(d[29]),"+f"(d[30]),"+f"(d[31]),"+f"(d[32]),"+f"(d[33]),"+f"(d[34]),"+f"(d[35]),"+f"(d[36]),"+f"(d[37]),"+f"(d[38]),"+f"(d[39]),"+f"(d[40]),"+f"(d[41]),"+f"(d[42]),"+f"(d[43]),"+f"(d[44]),"+f"(d[45]),"+f"(d[46]),"+f"(d[47]),"+f"(d[48]),"+f"(d[49]),"+f"(d[50]),"+f"(d[51]),"+f"(d[52]),"+f"(d[53]),"+f"(d[54]),"+f"(d[55]),"+f"(d[56]),"+f"(d[57]),"+f"(d[58]),"+f"(d[59]),"+f"(d[60]),"+f"(d[61]),"+f"(d[62]),"+f"(d[63])
   : "r"(alo), "r"(ahi), "r"(blo), "r"(bhi), "r"(sc), "n"(TA), "n"(TB));
}
template<int TA,int TB> __device__ __forceinline__ void wgmma_ss_64(float (&d)[32], uint32_t alo, uint32_t ahi, uint32_t blo, uint32_t bhi, int sc) {
  asm volatile("{\n.reg .pred p;\n.reg .b64 da, db;\nmov.b64 da, {%32, %33};\nmov.b64 db, {%34, %35};\nsetp.ne.b32 p, %36, 0;\n"
   "wgmma.mma_async.sync.aligned.m64n64k16.f32.bf16.bf16 {%0,%1,%2,%3,%4,%5,%6,%7,%8,%9,%10,%11,%12,%13,%14,%15,%16,%17,%18,%19,%20,%21,%22,%23,%24,%25,%26,%27,%28,%29,%30,%31}, da, db, p, 1, 1, %37, %38;\n}\n"
   : "+f"(d[0]),"+f"(d[1]),"+f"(d[2]),"+f"(d[3]),"+f"(d[4]),"+f"(d[5]),"+f"(d[6]),"+f"(d[7]),"+f"(d[8]),"+f"(d[9]),"+f"(d[10]),"+f"(d[11]),"+f"(d[12]),"+f"(d[13]),"+f"(d[14]),"+f"(d[15]),"+f"(d[16]),"+f"(d[17]),"+f"(d[18]),"+f"(d[19]),"+f"(d[20]),"+f"(d[21]),"+f"(d[22]),"+f"(d[23]),"+f"(d[24]),"+f"(d[25]),"+f"(d[26]),"+f"(d[27]),"+f"(d[28]),"+f"(d[29]),"+f"(d[30]),"+f"(d[31])
   : "r"(alo), "r"(ahi), "r"(blo), "r"(bhi), "r"(sc), "n"(TA), "n"(TB));
}
template<int TA,int TB> __device__ __forceinline__ void wgmma_ss_48(float (&d)[24], uint32_t alo, uint32_t ahi, uint32_t blo, uint32_t bhi, int sc) {
  asm volatile("{\n.reg .pred p;\n.reg .b64 da, db;\nmov.b64 da, {%24, %25};\nmov.b64 db, {%26, %27};\nsetp.ne.b32 p, %28, 0;\n"
   "wgmma.mma_async.sync.aligned.m64n48k16.f32.bf16.bf16 {%0,%1,%2,%3,%4,%5,%6,%7,%8,%9,%10,%11,%12,%13,%14,%15,%16,%17,%18,%19,%20,%21,%22,%23}, da, db, p, 1, 1, %29, %30;\n}\n"
   : "+f"(d[0]),"+f"(d[1]),"+f"(d[2]),"+f"(d[3]),"+f"(d[4]),"+f"(d[5]),"+f"(d[6]),"+f"(d[7]),"+f"(d[8]),"+f"(d[9]),"+f"(d[10]),"+f"(d[11]),"+f"(d[12]),"+f"(d[13]),"+f"(d[14]),"+f"(d[15]),"+f"(d[16]),"+f"(d[17]),"+f"(d[18]),"+f"(d[19]),"+f"(d[20]),"+f"(d[21]),"+f"(d[22]),"+f"(d[23])
   : "r"(alo), "r"(ahi), "r"(blo), "r"(bhi), "r"(sc), "n"(TA), "n"(TB));
}
template<int N> __device__ __forceinline__ void wgmma_rs(float (&d)[64], uint32_t a0, uint32_t a1, uint32_t a2, uint32_t a3, uint32_t blo, uint32_t bhi, int sc);
template<> __device__ __forceinline__ void wgmma_rs<128>(float (&d)[64], uint32_t a0, uint32_t a1, uint32_t a2, uint32_t a3, uint32_t blo, uint32_t bhi, int sc) {
  asm volatile("{\n.reg .pred p;\n.reg .b64 db;\nmov.b64 db, {%68, %69};\nsetp.ne.b32 p, %70, 0;\n"
   "wgmma.mma_async.sync.aligned.m64n128k16.f32.bf16.bf16 {%0,%1,%2,%3,%4,%5,%6,%7,%8,%9,%10,%11,%12,%13,%14,%15,%16,%17,%18,%19,%20,%21,%22,%23,%24,%25,%26,%27,%28,%29,%30,%31,%32,%33,%34,%35,%36,%37,%38,%39,%40,%41,%42,%43,%44,%45,%46,%47,%48,%49,%50,%51,%52,%53,%54,%55,%56,%57,%58,%59,%60,%61,%62,%63}, {%64,%65,%66,%67}, db, p, 1, 1, 0;\n}\n"
   : "+f"(d[0]),"+f"(d[1]),"+f"(d[2]),"+f"(d[3]),"+f"(d[4]),"+f"(d[5]),"+f"(d[6]),"+f"(d[7]),"+f"(d[8]),"+f"(d[9]),"+f"(d[10]),"+f"(d[11]),"+f"(d[12]),"+f"(d[13]),"+f"(d[14]),"+f"(d[15]),"+f"(d[16]),"+f"(d[17]),"+f"(d[18]),"+f"(d[19]),"+f"(d[20]),"+f"(d[21]),"+f"(d[22]),"+f"(d[23]),"+f"(d[24]),"+f"(d[25]),"+f"(d[26]),"+f"(d[27]),"+f"(d[28]),"+f"(d[29]),"+f"(d[30]),"+f"(d[31]),"+f"(d[32]),"+f"(d[33]),"+f"(d[34]),"+f"(d[35]),"+f"(d[36]),"+f"(d[37]),"+f"(d[38]),"+f"(d[39]),"+f"(d[40]),"+f"(d[41]),"+f"(d[42]),"+f"(d[43]),"+f"(d[44]),"+f"(d[45]),"+f"(d[46]),"+f"(d[47]),"+f"(d[48]),"+f"(d[49]),"+f"(d[50]),"+f"(d[51]),"+f"(d[52]),"+f"(d[53]),"+f"(d[54]),"+f"(d[55]),"+f"(d[56]),"+f"(d[57]),"+f"(d[58]),"+f"(d[59]),"+f"(d[60]),"+f"(d[61]),"+f"(d[62]),"+f"(d[63])
   : "r"(a0), "r"(a1), "r"(a2), "r"(a3), "r"(blo), "r"(bhi), "r"(sc));
}
template<> __device__ __forceinline__ void wgmma_rs<96>(float (&d)[64], uint32_t a0, uint32_t a1, uint32_t a2, uint32_t a3, uint32_t blo, uint32_t bhi, int sc) {
  asm volatile("{\n.reg .pred p;\n.reg .b64 db;\nmov.b64 db, {%52, %53};\nsetp.ne.b32 p, %54, 0;\n"
   "wgmma.mma_async.sync.aligned.m64n96k16.f32.bf16.bf16 {%0,%1,%2,%3,%4,%5,%6,%7,%8,%9,%10,%11,%12,%13,%14,%15,%16,%17,%18,%19,%20,%21,%22,%23,%24,%25,%26,%27,%28,%29,%30,%31,%32,%33,%34,%35,%36,%37,%38,%39,%40,%41,%42,%43,%44,%45,%46,%47}, {%48,%49,%50,%51}, db, p, 1, 1, 0;\n}\n"
   : "+f"(d[0]),"+f"(d[1]),"+f"(d[2]),"+f"(d[3]),"+f"(d[4]),"+f"(d[5]),"+f"(d[6]),"+f"(d[7]),"+f"(d[8]),"+f"(d[9]),"+f"(d[10]),"+f"(d[11]),"+f"(d[12]),"+f"(d[13]),"+f"(d[14]),"+f"(d[15]),"+f"(d[16]),"+f"(d[17]),"+f"(d[18]),"+f"(d[19]),"+f"(d[20]),"+f"(d[21]),"+f"(d[22]),"+f"(d[23]),"+f"(d[24]),"+f"(d[25]),"+f"(d[26]),"+f"(d[27]),"+f"(d[28]),"+f"(d[29]),"+f"(d[30]),"+f"(d[31]),"+f"(d[32]),"+f"(d[33]),"+f"(d[34]),"+f"(d[35]),"+f"(d[36]),"+f"(d[37]),"+f"(d[38]),"+f"(d[39]),"+f"(d[40]),"+f"(d[41]),"+f"(d[42]),"+f"(d[43]),"+f"(d[44]),"+f"(d[45]),"+f"(d[46]),"+f"(d[47])
   : "r"(a0), "r"(a1), "r"(a2), "r"(a3), "r"(blo), "r"(bhi), "r"(sc));
}
template<> __device__ __forceinline__ void wgmma_rs<64>(float (&d)[64], uint32_t a0, uint32_t a1, uint32_t a2, uint32_t a3, uint32_t blo, uint32_t bhi, int sc) {
  asm volatile("{\n.reg .pred p;\n.reg .b64 db;\nmov.b64 db, {%36, %37};\nsetp.ne.b32 p, %38, 0;\n"
   "wgmma.mma_async.sync.aligned.m64n64k16.f32.bf16.bf16 {%0,%1,%2,%3,%4,%5,%6,%7,%8,%9,%10,%11,%12,%13,%14,%15,%16,%17,%18,%19,%20,%21,%22,%23,%24,%25,%26,%27,%28,%29,%30,%31}, {%32,%33,%34,%35}, db, p, 1, 1, 0;\n}\n"
   : "+f"(d[0]),"+f"(d[1]),"+f"(d[2]),"+f"(d[3]),"+f"(d[4]),"+f"(d[5]),"+f"(d[6]),"+f"(d[7]),"+f"(d[8]),"+f"(d[9]),"+f"(d[10]),"+f"(d[11]),"+f"(d[12]),"+f"(d[13]),"+f"(d[14]),"+f"(d[15]),"+f"(d[16]),"+f"(d[17]),"+f"(d[18]),"+f"(d[19]),"+f"(d[20]),"+f"(d[21]),"+f"(d[22]),"+f"(d[23]),"+f"(d[24]),"+f"(d[25]),"+f"(d[26]),"+f"(d[27]),"+f"(d[28]),"+f"(d[29]),"+f"(d[30]),"+f"(d[31])
   : "r"(a0), "r"(a1), "r"(a2), "r"(a3), "r"(blo), "r"(bhi), "r"(sc));
}
template<> __device__ __forceinline__ void wgmma_rs<32>(float (&d)[64], uint32_t a0, uint32_t a1, uint32_t a2, uint32_t a3, uint32_t blo, uint32_t bhi, int sc) {
  asm volatile("{\n.reg .pred p;\n.reg .b64 db;\nmov.b64 db, {%20, %21};\nsetp.ne.b32 p, %22, 0;\n"
   "wgmma.mma_async.sync.aligned.m64n32k16.f32.bf16.bf16 {%0,%1,%2,%3,%4,%5,%6,%7,%8,%9,%10,%11,%12,%13,%14,%15}, {%16,%17,%18,%19}, db, p, 1, 1, 0;\n}\n"
   : "+f"(d[0]),"+f"(d[1]),"+f"(d[2]),"+f"(d[3]),"+f"(d[4]),"+f"(d[5]),"+f"(d[6]),"+f"(d[7]),"+f"(d[8]),"+f"(d[9]),"+f"(d[10]),"+f"(d[11]),"+f"(d[12]),"+f"(d[13]),"+f"(d[14]),"+f"(d[15])
   : "r"(a0), "r"(a1), "r"(a2), "r"(a3), "r"(blo), "r"(bhi), "r"(sc));
}
__device__ __forceinline__ void wgmma_rs128z(float (&d)[64], uint32_t a0, uint32_t a1, uint32_t a2, uint32_t a3, uint32_t blo, uint32_t bhi, int sc) {
  asm volatile("{\n.reg .pred p;\n.reg .b64 db;\nmov.b64 db, {%68, %69};\nsetp.ne.b32 p, %70, 0;\n"
   "wgmma.mma_async.sync.aligned.m64n128k16.f32.bf16.bf16 {%0,%1,%2,%3,%4,%5,%6,%7,%8,%9,%10,%11,%12,%13,%14,%15,%16,%17,%18,%19,%20,%21,%22,%23,%24,%25,%26,%27,%28,%29,%30,%31,%32,%33,%34,%35,%36,%37,%38,%39,%40,%41,%42,%43,%44,%45,%46,%47,%48,%49,%50,%51,%52,%53,%54,%55,%56,%57,%58,%59,%60,%61,%62,%63}, {%64,%65,%66,%67}, db, p, 1, 1, 0;\n}\n"
   : "=f"(d[0]),"=f"(d[1]),"=f"(d[2]),"=f"(d[3]),"=f"(d[4]),"=f"(d[5]),"=f"(d[6]),"=f"(d[7]),"=f"(d[8]),"=f"(d[9]),"=f"(d[10]),"=f"(d[11]),"=f"(d[12]),"=f"(d[13]),"=f"(d[14]),"=f"(d[15]),"=f"(d[16]),"=f"(d[17]),"=f"(d[18]),"=f"(d[19]),"=f"(d[20]),"=f"(d[21]),"=f"(d[22]),"=f"(d[23]),"=f"(d[24]),"=f"(d[25]),"=f"(d[26]),"=f"(d[27]),"=f"(d[28]),"=f"(d[29]),"=f"(d[30]),"=f"(d[31]),"=f"(d[32]),"=f"(d[33]),"=f"(d[34]),"=f"(d[35]),"=f"(d[36]),"=f"(d[37]),"=f"(d[38]),"=f"(d[39]),"=f"(d[40]),"=f"(d[41]),"=f"(d[42]),"=f"(d[43]),"=f"(d[44]),"=f"(d[45]),"=f"(d[46]),"=f"(d[47]),"=f"(d[48]),"=f"(d[49]),"=f"(d[50]),"=f"(d[51]),"=f"(d[52]),"=f"(d[53]),"=f"(d[54]),"=f"(d[55]),"=f"(d[56]),"=f"(d[57]),"=f"(d[58]),"=f"(d[59]),"=f"(d[60]),"=f"(d[61]),"=f"(d[62]),"=f"(d[63])
   : "r"(a0), "r"(a1), "r"(a2), "r"(a3), "r"(blo), "r"(bhi), "r"(sc));
}

__device__ __forceinline__ void wg_fence()  { asm volatile("wgmma.fence.sync.aligned;" ::: "memory"); }
__device__ __forceinline__ void wg_commit() { asm volatile("wgmma.commit_group.sync.aligned;" ::: "memory"); }
template<int N> __device__ __forceinline__ void wg_wait() { asm volatile("wgmma.wait_group.sync.aligned %0;" :: "n"(N) : "memory"); }
template<int N> __device__ __forceinline__ void pin(float (&d)[N]) {
#pragma unroll
  for (int i = 0; i < N; i++) asm volatile("" : "+f"(d[i]) :: "memory");
}
__host__ __device__ constexpr uint32_t dlo(uint32_t addr, uint32_t lbo) { return (addr >> 4) | ((lbo >> 4) << 16); }
constexpr uint32_t HI128 = (1024 >> 4) | (1u << 30), HI64 = (512 >> 4) | (2u << 30), HI0 = 128 >> 4;
__device__ __forceinline__ void mbar_init(uint32_t b, int c) { asm volatile("mbarrier.init.shared::cta.b64 [%0], %1;" :: "r"(b), "r"(c) : "memory"); }
__device__ __forceinline__ void mbar_expect(uint32_t b, int bytes) { asm volatile("mbarrier.arrive.expect_tx.shared::cta.b64 _, [%0], %1;" :: "r"(b), "r"(bytes) : "memory"); }
__device__ __forceinline__ void mbar_arrive(uint32_t b) { asm volatile("mbarrier.arrive.shared::cta.b64 _, [%0];" :: "r"(b) : "memory"); }
__device__ __forceinline__ void mbar_wait(uint32_t b, uint32_t par, int& n) {
  asm volatile("{\n.reg .pred p;\nW:\nmbarrier.try_wait.parity.shared::cta.b64 p, [%1], %2;\nadd.s32 %0, %0, -1;\n"
               "setp.gt.and.s32 p, %0, 0, !p;\n@p bra.uni W;\n}" : "+r"(n) : "r"(b), "r"(par) : "memory");
}
__device__ __forceinline__ bool elect() {
  uint32_t r;
  asm volatile("{\n.reg .pred p;\nelect.sync _|p, 0xFFFFFFFF;\nselp.u32 %0, 1, 0, p;\n}" : "=r"(r));
  return r;
}
__device__ __forceinline__ void tma2d(uint32_t dst, const CUtensorMap* tm, int c0, int c1, uint32_t bar) {
  asm volatile("cp.async.bulk.tensor.2d.shared::cluster.global.mbarrier::complete_tx::bytes [%0], [%1, {%2, %3}], [%4];"
               :: "r"(dst), "l"(tm), "r"(c0), "r"(c1), "r"(bar) : "memory");
}
__device__ __forceinline__ void tma5d(uint32_t dst, const CUtensorMap* tm, int c0, int c4, uint32_t bar) {
  asm volatile("cp.async.bulk.tensor.5d.shared::cluster.global.mbarrier::complete_tx::bytes [%0], [%1, {%2, %3, %3, %3, %4}], [%5];"
               :: "r"(dst), "l"(tm), "r"(c0), "r"(0), "r"(c4), "r"(bar) : "memory");
}
__device__ __forceinline__ void bulk_load(uint32_t dst, const void* src, int bytes, uint32_t bar) {
  asm volatile("cp.async.bulk.shared::cluster.global.mbarrier::complete_tx::bytes [%0], [%1], %2, [%3];"
               :: "r"(dst), "l"(src), "r"(bytes), "r"(bar) : "memory");
}
__device__ __forceinline__ void l2_prefetch(const void* src, int bytes) {
  asm volatile("cp.async.bulk.prefetch.L2.global [%0], %1;" :: "l"(src), "r"(bytes) : "memory");
}
__device__ __forceinline__ void tm_prefetch(const CUtensorMap* tm) { asm volatile("prefetch.tensormap [%0];" :: "l"(tm) : "memory"); }
__device__ __forceinline__ void fence_async_smem() { asm volatile("fence.proxy.async.shared::cta;" ::: "memory"); }
__device__ __forceinline__ void fence_async_glob() { asm volatile("fence.proxy.async.global;" ::: "memory"); }
template<int ID, int N> __device__ __forceinline__ void bar_sync()   { asm volatile("bar.sync %0, %1;" :: "n"(ID), "n"(N) : "memory"); }
template<int ID, int N> __device__ __forceinline__ void bar_arrive() { asm volatile("bar.arrive %0, %1;" :: "n"(ID), "n"(N) : "memory"); }
__device__ __forceinline__ void bar_sync_r(int id, int n)   { asm volatile("bar.sync %0, %1;" :: "r"(id), "r"(n) : "memory"); }
__device__ __forceinline__ void bar_arrive_r(int id, int n) { asm volatile("bar.arrive %0, %1;" :: "r"(id), "r"(n) : "memory"); }
__device__ __forceinline__ void red_release(uint32_t* p, uint32_t v) { asm volatile("red.release.gpu.global.add.u32 [%0], %1;" :: "l"(p), "r"(v) : "memory"); }
__device__ __forceinline__ uint32_t ld_acquire(const uint32_t* p) { uint32_t v; asm volatile("ld.acquire.gpu.global.u32 %0, [%1];" : "=r"(v) : "l"(p) : "memory"); return v; }
__device__ __forceinline__ uint32_t ldg16(const void* p) { uint16_t v; asm volatile("ld.global.nc.u16 %0, [%1];" : "=h"(v) : "l"(p)); return v; }
__device__ __forceinline__ uint2 ldg64(const void* p) { uint2 v; asm volatile("ld.global.nc.v2.u32 {%0,%1}, [%2];" : "=r"(v.x), "=r"(v.y) : "l"(p)); return v; }
template<typename T> __device__ __forceinline__ T* fix(T* p) { asm volatile("" : "+l"(p)); return p; }
__device__ __forceinline__ uint32_t lds32(uint32_t a) { uint32_t v; asm volatile("ld.shared.u32 %0, [%1];" : "=r"(v) : "r"(a) : "memory"); return v; }
__device__ __forceinline__ uint32_t lds16(uint32_t a) { uint16_t v; asm volatile("ld.shared.u16 %0, [%1];" : "=h"(v) : "r"(a) : "memory"); return v; }
__device__ __forceinline__ uint4 lds128(uint32_t a) { uint4 v; asm volatile("ld.shared.v4.u32 {%0,%1,%2,%3}, [%4];" : "=r"(v.x), "=r"(v.y), "=r"(v.z), "=r"(v.w) : "r"(a) : "memory"); return v; }
__device__ __forceinline__ void sts16(uint32_t a, uint32_t v) { asm volatile("st.shared.u16 [%0], %1;" :: "r"(a), "h"((uint16_t)v) : "memory"); }
__device__ __forceinline__ void sts32(uint32_t a, uint32_t v) { asm volatile("st.shared.u32 [%0], %1;" :: "r"(a), "r"(v) : "memory"); }
__device__ __forceinline__ void sts128(uint32_t a, uint32_t x, uint32_t y, uint32_t z, uint32_t w) { asm volatile("st.shared.v4.u32 [%0], {%1,%2,%3,%4};" :: "r"(a), "r"(x), "r"(y), "r"(z), "r"(w) : "memory"); }
__device__ __forceinline__ uint32_t pack2(float lo, float hi)      { uint32_t r; asm("cvt.rn.bf16x2.f32 %0, %1, %2;" : "=r"(r) : "f"(hi), "f"(lo)); return r; }
__device__ __forceinline__ uint32_t pack2relu(float lo, float hi)  { uint32_t r; asm("cvt.rn.relu.bf16x2.f32 %0, %1, %2;" : "=r"(r) : "f"(hi), "f"(lo)); return r; }
__device__ __forceinline__ uint32_t mul2(uint32_t a, uint32_t b) { uint32_t r; asm("mul.rn.bf16x2 %0, %1, %2;" : "=r"(r) : "r"(a), "r"(b)); return r; }
__device__ __forceinline__ uint32_t fma2(uint32_t a, uint32_t b, uint32_t c) { uint32_t r; asm("fma.rn.bf16x2 %0, %1, %2, %3;" : "=r"(r) : "r"(a), "r"(b), "r"(c)); return r; }
__device__ __forceinline__ uint32_t sub2(uint32_t a, uint32_t b) { uint32_t r; asm("sub.rn.bf16x2 %0, %1, %2;" : "=r"(r) : "r"(a), "r"(b)); return r; }
__device__ __forceinline__ float bflo(uint32_t v) { return __uint_as_float(v << 16); }
__device__ __forceinline__ float bfhi(uint32_t v) { return __uint_as_float(v & 0xFFFF0000u); }
__device__ __forceinline__ float bfround(float x) { return __uint_as_float(pack2(0.f, x)); }
__device__ __forceinline__ uint32_t pair(uint32_t lo, uint32_t hi) { return __byte_perm(lo, hi, 0x5410); }
__device__ __forceinline__ float ex2(float x) { float r; asm("ex2.approx.ftz.f32 %0, %1;" : "=f"(r) : "f"(x)); return r; }
__device__ __forceinline__ float2 cexp(float al, float om) {
  const float mag = ex2(al);
  return make_float2(mag * __cosf(om), mag * __sinf(om));
}
__device__ __forceinline__ float2 cmul(float2 a, float2 b) {
  return make_float2(fmaf(a.x, b.x, -a.y * b.y), fmaf(a.x, b.y, a.y * b.x));
}

struct Params {
  CUtensorMap tm[7];
  const uint2 *lar, *aim, *cre, *cim, *gw;
  const __nv_bfloat16 *ldt, *dskip, *wg, *wu, *wd;
};

template<int J, int UP, int RH, int N> __device__ __forceinline__ uint4 h_chunk(float (&acc)[N]) {
  uint32_t v[4];
#pragma unroll
  for (int jl = 0; jl < 4; jl++) {
    const int i = 4 * (J + jl) + 2 * RH;
    v[jl] = mul2(pack2relu(acc[i], acc[i + 1]), pack2(acc[UP + i], acc[UP + i + 1]));
  }
  return make_uint4(v[0], v[1], v[2], v[3]);
}
template<int H> __device__ __forceinline__ void conv_load(uint32_t (&A)[16], uint32_t pa) {
#pragma unroll
  for (int jj = 0; jj < 8; jj++) {
    const uint32_t a = pa + 2176 * (H >> 1) + 128 * (4 * (H & 1) + (jj >> 1)) + 16 * (~jj & 1);
    asm volatile("ld.shared.v2.u32 {%0,%1}, [%2];" : "=r"(A[2 * jj]), "=r"(A[2 * jj + 1]) : "r"(a) : "memory");
  }
}
template<int H> __device__ __forceinline__ void conv_mma(float (&acc)[64], uint32_t (&A)[16], uint32_t blo) {
  wg_fence();
#pragma unroll
  for (int jj = 0; jj < 4; jj++)
    if ((H | jj) == 0) wgmma_rs128z(acc, A[0], A[1], A[2], A[3], blo, HI0, 0); else
    wgmma_rs<128 - 32 * (H >> 1)>(acc, A[4 * jj], A[4 * jj + 1], A[4 * jj + 2], A[4 * jj + 3], blo + 32 * (H >> 1) + 4 * (H & 1) + jj, HI0, 1);
  wg_commit();
}
struct Tab { uint32_t a0, a1, a2, a3, b0, b2, d0, d2, ta, p0, p1; };
template<int IT> __device__ __forceinline__ void tab_step(uint32_t ka, Tab& t, int tid) {
  uint32_t v[4];
  if (IT == 0) {
    uint32_t w0 = lds32(ka + t.a3 - 4);
    const uint32_t w1 = lds32(ka + t.a3), L = lds16(ka + t.a0), T = lds16(ka + t.a1), H = lds16(ka + t.a2);
    if (tid == 0) w0 = 0;
    v[0] = __byte_perm(w0, w1, 0x3254); v[2] = __byte_perm(w0, w1, 0x5476); v[1] = pair(T, L); v[3] = pair(H, T);
    t.p0 = t.p1 = 0;
  } else {
#pragma unroll
    for (int h = 0; h < 2; h++) {
      const uint32_t o = IT == 1 ? 128 * h : 128 * IT + 64 * h;
      const uint32_t L = lds16(ka + (IT == 1 ? t.b0 : t.d0) + o), H = lds16(ka + (IT == 1 ? t.b2 : t.d2) + o), T = (tid & (IT == 1 ? 2 : 4)) ? H : L;
      v[h] = pair(T, L); v[2 + h] = pair(H, T);
    }
  }
  const uint32_t a = t.ta + 2176 * IT;
  sts128(a, v[0], v[1], v[2], v[3]);
  if (tid >= 120) { sts32(a - 2048, t.p0); sts32(a - 2044, v[0]); sts32(a - 2040, t.p1); sts32(a - 2036, v[2]); }
  t.p0 = v[1]; t.p1 = v[3];
}
__device__ __forceinline__ void sts_re(uint32_t a, const float2 (&v)[8]) { sts128(a, pack2(v[0].x, v[1].x), pack2(v[2].x, v[3].x), pack2(v[4].x, v[5].x), pack2(v[6].x, v[7].x)); }
__device__ __forceinline__ void sts_im(uint32_t a, const float2 (&v)[8]) { sts128(a, pack2(v[0].y, v[1].y), pack2(v[2].y, v[3].y), pack2(v[4].y, v[5].y), pack2(v[6].y, v[7].y)); }
__device__ __forceinline__ uint32_t pack2sel(float a, float b, float c, float d, int s) {
  uint32_t r;
  asm("{\n.reg .pred p;\nsetp.ne.b32 p, %5, 0;\ncvt.rn.bf16x2.f32 %0, %2, %1;\n@p cvt.rn.bf16x2.f32 %0, %4, %3;\n}" : "=&r"(r) : "f"(a), "f"(b), "f"(c), "f"(d), "r"(s));
  return r;
}

__global__ void __launch_bounds__(512, 1) fused_kernel(const __grid_constant__ Params p) {
  const int cta = blockIdx.x, m = cta >> 3, f = cta & 7;
  const int wid = __shfl_sync(~0u, threadIdx.x >> 5, 0);
  const int wgi = wid >> 2, w = wid & 3, tid = threadIdx.x & 127, lane = tid & 31, g = lane >> 2, q = lane & 3;
  int n = 1 << 17;
  PT(0, wgi); PG(110);
  if (wgi != 2) {
    if (wid < 7) tm_prefetch(&p.tm[wid]);
    const uint32_t bb = wgi < 2 ? B_WE + 24 * wid : B_GF + 32 * w;
#pragma unroll
    for (int i = 0; i < 3; i++) mbar_init(bb + 8 * i, max(4 >> wgi, 1));
    if (wgi == 3) mbar_init(bb + 24, 1);
    fence_async_smem();
    bar_sync<0, 384>();
    PT(0, 109);
  }

  if (wgi < 2) {
    asm volatile("setmaxnreg.inc.sync.aligned.u32 " STR(RG) ";");
    uint4* hp = g_t + (m * TPM + f + 8 * wgi) * 1024 + 64 * g + 8 * (3 - w) + (q ^ (3 - w));
    if (wgi == 1) {
      const uint2 gw = __ldg(p.gw + ((tid + 16 * f) & 127));
      g_ut[(128 * f + 8 * m + ((tid >> 3) & 7)) * 136 + 128 + (tid & 7)] = make_uint4(0, 0, 0, 0);
      uint4* up = g_ut + (64 * f + g) * 272 + (q & 1) * 136 + 127 - (8 * m + 2 * w + (q >> 1));
      const int tl = 32 * w + 16 * ((lane >> 2) & 1) + 4 * (lane >> 3) + (lane & 3);
      const uint32_t la = SM_X + tl * 128 + ((tl & 7) << 4);
      mbar_wait(B_XF, 0, n);
#pragma unroll
      for (int dg = 0; dg < 8; dg++) {
        uint4 v;
        asm volatile("ldmatrix.sync.aligned.m8n8.x4.trans.shared.b16 {%0,%1,%2,%3}, [%4];"
                     : "=r"(v.x), "=r"(v.y), "=r"(v.z), "=r"(v.w) : "r"(la ^ (dg << 4)) : "memory");
        up[dg * 2176] = v;
      }
      bar_arrive<8, 160>();
      asm volatile("st.shared.v2.u32 [%0], {%1,%2};" :: "r"(SM_GW + 8 * tid), "r"(gw.x), "r"(gw.y) : "memory");
      PT(1, 80);
    }
    hp = fix(hp);
    constexpr uint32_t dX = dlo(SM_X, 16);
    {
      constexpr uint32_t dW = dlo(SM_W, 8192);
      float acc0[64], acc1[64];
#pragma unroll 1
      for (int ui = wgi; ui < 3; ui += 2) {
        if (ui) bar_sync_r(ui, 256);
#pragma unroll 1
        for (int k = 0; k < 8; k++) {
          if (ui == 0) mbar_wait(B_XF + 8 * k, 0, n);
          mbar_wait(B_WF + 8 * (k & 3), k >> 2, n);
          PT(2, 84 + 8 * ui + k);
          wg_fence();
#pragma unroll
          for (int kk = 0; kk < 4; kk++) {
            wgmma_ss_128<0, 1>(acc0, dX + k * 1024 + kk * 2, HI128, dW + (k & 3) * 1024 + kk * 128, HI128, (k | kk) != 0);
            wgmma_ss_128<0, 1>(acc1, dX + k * 1024 + 512 + kk * 2, HI128, dW + (k & 3) * 1024 + kk * 128, HI128, (k | kk) != 0);
          }
          wg_commit();
          if (k == 7) bar_arrive_r(ui + 1, 256);
          wg_wait<1>();
          if (k > 0 && lane == 0) mbar_arrive(B_WE + 8 * ((k - 1) & 3));
        }
        wg_wait<0>();
        pin(acc0); pin(acc1);
        if (lane == 0) mbar_arrive(B_WE + 8 * 3);
        PT(3, 8 + ui);
        hp[36]      = h_chunk<0, 32, 0>(acc0); hp[32]      = h_chunk<4, 32, 0>(acc0);
        hp[36 + 512] = h_chunk<0, 32, 1>(acc0); hp[32 + 512] = h_chunk<4, 32, 1>(acc0);
        hp[0]       = h_chunk<0, 32, 0>(acc1); hp[4]       = h_chunk<4, 32, 0>(acc1);
        hp[512]     = h_chunk<0, 32, 1>(acc1); hp[4 + 512] = h_chunk<4, 32, 1>(acc1);
        bar_arrive_r(9 + ui, 160);
        hp += 16 * 1024;
        PT(3, 12 + ui);
      }
    }
    if (wgi == 1) {
      {
        const int r = 2 * f + (tid >> 6), c = (tid >> 3) & 7;
        const uint32_t xa = SM_X + (16 * (7 - c) + r) * 128 + (((tid ^ r) & 7) << 4), ga = SM_GW + (tid & 7) * 16;
        float s = 0.f;
#pragma unroll 1
        for (int k = 0; k < 8; k++) {
          const uint4 xv = lds128(xa + k * 16384), gw = lds128(ga + k * 128);
          const uint32_t p0 = mul2(xv.x, gw.x), p1 = mul2(xv.y, gw.y), p2 = mul2(xv.z, gw.z), p3 = mul2(xv.w, gw.w);
          s += ((bflo(p0) + bfhi(p0)) + (bflo(p1) + bfhi(p1))) + ((bflo(p2) + bfhi(p2)) + (bflo(p3) + bfhi(p3)));
        }
        s += __shfl_xor_sync(~0u, s, 1); s += __shfl_xor_sync(~0u, s, 2); s += __shfl_xor_sync(~0u, s, 4);
        const float gv = __fdividef(1.f, 1.f + ex2(bfround(s) * -1.4426950408889634f));
        ((uint16_t*)(g_t + (m * TPM + 28) * 1024))[(r >> 2) * 32 + (c >> 1) * 8 + (r & 3) * 2 + (c & 1)] = (uint16_t)pack2(gv, 0.f);
        PT(1, 82);
      }
      constexpr uint32_t dW = dlo(SM_W, 4096);
      hp += ((f >> 1) - f) * 1024;
      uint4* h0 = fix(hp + 36 - 4 * (f & 1));
      uint4* h1 = fix(hp + 4 * (f & 1));
      float acc0[32], acc1[32];
      bar_sync<3, 256>();
#pragma unroll 1
      for (int k = 0; k < 8; k++) {
        mbar_wait(B_XF + 8 * k, 1, n);
        PT(2, 70 + k);
        wg_fence();
#pragma unroll
        for (int kk = 0; kk < 4; kk++) {
          wgmma_ss_64<0, 1>(acc0, dX + k * 1024 + kk * 2, HI128, dW + k * 512 + kk * 64, HI64, (k | kk) != 0);
          wgmma_ss_64<0, 1>(acc1, dX + k * 1024 + 512 + kk * 2, HI128, dW + k * 512 + kk * 64, HI64, (k | kk) != 0);
        }
        wg_commit();
        wg_wait<1>();
        if (k > 0 && lane == 0) mbar_arrive(B_GE + 8 * k - 8);
      }
      wg_wait<0>();
      pin(acc0); pin(acc1);
      if (lane == 0) mbar_arrive(B_GE + 56);
      PT(3, 11);
      h0[0] = h_chunk<0, 16, 0>(acc0); h0[512] = h_chunk<0, 16, 1>(acc0);
      h1[0] = h_chunk<0, 16, 0>(acc1); h1[512] = h_chunk<0, 16, 1>(acc1);
      bar_arrive<12, 160>();
      PT(3, 15);
    } else {
      float acc[64];
      constexpr uint32_t dA = dlo(SM_W, 16);
#pragma unroll 1
      for (int i = 0; i < 28; i++) {
        const int sl = i & 7;
        mbar_wait(B_GF + 8 * sl, (i >> 3) & 1, n);
        PT(4, 20 + i);
        wg_fence();
#pragma unroll
        for (int kk = 0; kk < 4; kk++) wgmma_ss_128<1, 0>(acc, dA + sl * 512 + kk * 128, HI128, dX + sl * 1024 + kk * 2, HI128, (i | kk) != 0);
        wg_commit();
        wg_wait<1>();
        if (i >= LAG && lane == 0) mbar_arrive(B_GE + 8 * ((i - LAG) & 7));
      }
      mbar_wait(B_GF + 32, 1, n);
      mbar_wait(B_GF + 40, 1, n);
      PT(4, 16);
      uint4 av[8], gv[4];
#pragma unroll
      for (int c = 0; c < 8; c++) av[c] = lds128(SM_X + 5 * 16384 + w * 4096 + (g >> 1) * 512 + (lane & 7) * 16 + (c >> 2) * 2048 + (c & 3) * 128);
#pragma unroll
      for (int c = 0; c < 4; c++) gv[c] = lds128(SM_X + 4 * 16384 + q * 16 + c * 64);
      wg_wait<0>();
      pin(acc);
      PT(4, 18);
      const uint32_t oa = SM_OUT + ((lane >> 4) * 8 + 7 - (lane & 7)) * 128 + (((2 * w + ((lane >> 3) & 1)) ^ (7 - (lane & 7))) << 4);
#pragma unroll
      for (int i2 = 0; i2 < 8; i2++) {
        uint32_t r[4];
#pragma unroll
        for (int e = 0; e < 4; e++) {
          const int i = 2 * i2 + (e >> 1);
          const uint32_t b = pack2(acc[4 * i + 2 * (e & 1)], acc[4 * i + 2 * (e & 1) + 1]);
          r[e] = fma2(((const uint32_t*)gv)[i], sub2(((const uint32_t*)av)[16 * (e & 1) + i], b), b);
        }
        asm volatile("stmatrix.sync.aligned.m8n8.x4.trans.shared.b16 [%0], {%1,%2,%3,%4};"
                     :: "r"(oa + i2 * 2048), "r"(r[0]), "r"(r[1]), "r"(r[2]), "r"(r[3]) : "memory");
      }
      fence_async_smem();
      bar_sync<5, 128>();
      if (w == 0 && elect()) {
        asm volatile("cp.async.bulk.tensor.3d.global.shared::cta.bulk_group [%0, {%1, %2, %3}], [%4];"
                     :: "l"(&p.tm[6]), "r"(f * 64), "r"(m * 8), "r"(0), "r"(SM_OUT) : "memory");
        asm volatile("cp.async.bulk.commit_group;" ::: "memory");
        asm volatile("cp.async.bulk.wait_group.read 0;" ::: "memory");
        PT(0, 19); PG(111);
      }
    }
  } else if (wgi == 2) {
    const uint2 lar = __ldg(p.lar + cta * 128 + tid), aim = __ldg(p.aim + cta * 128 + tid);
    const uint2 cre = __ldg(p.cre + cta * 128 + tid), cim = __ldg(p.cim + cta * 128 + tid);
    const uint32_t ldt = ldg16(p.ldt + 4 * cta + w), ds0 = ldg16(p.dskip + 4 * cta + (w >> 1)), ds1 = ldg16(p.dskip + 4 * cta + 2 + (w >> 1));
    asm volatile("setmaxnreg.inc.sync.aligned.u32 " STR(RC) ";");
    const bool hl = lane & 16;
    uint32_t* ap = fix((uint32_t*)g_t + ((hl ? 7 : 15) * TPM + 29 + (cta >> 4)) * 4096 + 256 * (cta & 15) + 32 * w + 4 * q + (g & 3));
    {
      const float dt = bfround(ex2(bflo(ldt) * 1.4426950408889634f));
      const uint32_t aa = SM_KA + (tid >> 6) * 8192 + (lane >> 3) * 2048 + (w & 1) * 512 + (lane & 7) * 16;
      const uint32_t ba = SM_KB + (tid >> 6) * 6144 + (lane >> 3) * 1536 + (w & 1) * 384 + (lane & 7) * 16;
      float kc0[24], kc1[24];
#pragma unroll 1
      for (int s = 0; s < 4; s++) {
        const uint32_t sel = 0x10 + 0x22 * s;
        const float ar = bfround(ex2(bflo(__byte_perm(lar.x, lar.y, sel)) * 1.4426950408889634f));
        const float al = (ar * dt) * -1.4426950408889634f, om = bflo(__byte_perm(aim.x, aim.y, sel)) * dt;
        float2 v[8], t[8], u[8], z[8];
        v[0] = make_float2(bflo(__byte_perm(cre.x, cre.y, sel)) * (2.f * dt), bflo(__byte_perm(cim.x, cim.y, sel)) * (2.f * dt));
        if (s == 0) PT(5, 48);
        const float2 z1 = cexp(al, om), z64 = cexp(al * 64.f, om * -64.f), z256 = cexp(al * 256.f, om * 256.f);
        z[0] = make_float2(1.f, 0.f); z[1] = cexp(al * 8.f, om * -8.f);
#pragma unroll
        for (int i = 1; i < 8; i++) v[i] = cmul(v[i - 1], z1);
#pragma unroll
        for (int i = 2; i < 8; i++) z[i] = cmul(z[i - 1], z[1]);
#pragma unroll
        for (int i = 0; i < 4; i++) t[i] = cmul(v[2 * i], z256);
        t[4] = cmul(t[0], z256); t[5] = cmul(t[2], z256); t[6] = cmul(t[4], z256); t[7] = cmul(t[5], z256);
        u[0] = cmul(t[6], z256);
#pragma unroll
        for (int i = 1; i < 5; i++) u[i] = cmul(u[i - 1], z256);
        u[5] = u[0]; u[6] = u[1]; u[7] = u[2];
        uint32_t bv[24];
#pragma unroll
        for (int i = 0; i < 4; i++) {
          bv[i]      = pack2(v[2 * i].x, v[2 * i + 1].x); bv[4 + i]  = pack2(t[2 * i].x, t[2 * i + 1].x); bv[8 + i]  = pack2(u[2 * i].x, u[2 * i + 1].x);
          bv[12 + i] = pack2(v[2 * i].y, v[2 * i + 1].y); bv[16 + i] = pack2(t[2 * i].y, t[2 * i + 1].y); bv[20 + i] = pack2(u[2 * i].y, u[2 * i + 1].y);
        }
#pragma unroll
        for (int i = 0; i < 24; i++) asm volatile("" : "+r"(bv[i]));
        asm volatile("" : "+f"(z[7].x), "+f"(z[7].y));
        if (s == SS) PT(8, 63);
        if (s) { wg_wait<0>(); bar_sync<4, 128>(); }
        if (s == SS) PT(8, 68);
#pragma unroll
        for (int i = 0; i < 6; i++) sts128(ba + 128 * i + (i > 2 ? 384 : 0), bv[4 * i], bv[4 * i + 1], bv[4 * i + 2], bv[4 * i + 3]);
#pragma unroll 1
        for (int j = 0;;) {
          sts_re(aa + j, z); sts_im(aa + j + 1024, z);
          j += 128;
          if (j == 512) break;
#pragma unroll
          for (int i = 0; i < 8; i++) {
            const float a = z[i].y * z64.y, b = z[i].x * z64.y;
            z[i].x = fmaf(z[i].x, z64.x, -a); z[i].y = fmaf(z[i].y, z64.x, b);
          }
        }
        if (s == SS) PT(8, 69);
        fence_async_smem();
        if (s == SS) PT(8, 81);
        bar_sync<4, 128>();
        if (s == SS) PT(8, 83);
        wg_fence();
#pragma unroll
        for (int ks = 0; ks < 4; ks++) {
          wgmma_ss_48<1, 1>(kc0, dlo(SM_KA + ks * 2048, 1024), HI0, dlo(SM_KB + ks * 1536, 768), HI0, (s | ks) != 0);
          wgmma_ss_48<1, 1>(kc1, dlo(SM_KA + 8192 + ks * 2048, 1024), HI0, dlo(SM_KB + 6144 + ks * 1536, 768), HI0, (s | ks) != 0);
        }
        wg_commit();
        PT(5, 64 + s);
      }
      const int row = 16 * (w & 1) + g;
      const uint32_t ka = SM_K + (w >> 1) * K_CH;
      const uint32_t k0 = ka + 16 * row + 4 * q, k1 = ka + 512 + (q < 2 ? 8 * row + 4 * q : 128 * q + 4 * row), k1b = k1 + (q < 2 ? 64 : 32);
      const uint32_t k2 = ka + 1024 + 128 * q + 2 * row;
      wg_wait<0>();
      pin(kc0); pin(kc1);
      if ((tid & 63) == 0) { kc0[0] += bflo(ds0); kc0[12] += bflo(ds0); kc1[0] += bflo(ds1); kc1[12] += bflo(ds1); }
#define KOUT(kc, o) _Pragma("unroll") for (int rh = 0; rh < 2; rh++) { \
        sts32(k0 + o + 128 * rh, pack2sel(kc[2 * rh], kc[2 * rh + 1], kc[12 + 2 * rh], kc[13 + 2 * rh], w & 2)); \
        sts32((rh ? k1b : k1) + o, pack2sel(kc[4 + 2 * rh], kc[5 + 2 * rh], kc[16 + 2 * rh], kc[17 + 2 * rh], w & 2)); \
        const uint32_t v = pack2sel(kc[8 + 2 * rh], kc[9 + 2 * rh], kc[20 + 2 * rh], kc[21 + 2 * rh], w & 2); \
        if (q < 3) sts16(k2 + o + 16 * rh, v); \
        if (q < 2) sts16(k2 + o + 64 + 16 * rh, v >> 16); }
      KOUT(kc0, 0)
      KOUT(kc1, 2 * K_CH)
    }
    bar_sync<15, 160>();
    PT(5, 50);
    if (w == 0 && elect()) {
      mbar_wait(B_HR, 0, n);
      bulk_load(SM_U, g_ut + cta * 1088, 8 * U_CP, B_UF);
      mbar_expect(B_UF, 8 * U_CP);
    }
    __syncwarp();
    Tab tb;
    tb.b0 = SM_K + 768 + (tid & ~1); tb.b2 = SM_K + 768 + ((tid + 1) & ~1);
    tb.a0 = SM_K + 512 + (tid ? 2 * (tid & ~1) : -2); tb.a1 = SM_K + 512 + 2 * tid; tb.a2 = SM_K + 512 + 2 * ((tid + 1) & ~1); tb.a3 = SM_K + 4 * tid;
    tb.d0 = SM_K + 768 + 2 * ((tid + 1) >> 2); tb.d2 = SM_K + 768 + 2 * ((tid + 2) >> 2);
    tb.ta = SM_T + 128 + 16 * tid;
    const uint32_t pa = SM_T + 8 * (128 * (g >> 2) + 14 + 4 * w + (g & 3) - 4 * q);
    uint32_t A0[16], A1[16];
    float acc[64];
    wg_fence(); wg_commit();
#pragma unroll 1
    for (int c = 0;; c++) {
      const uint32_t db = dlo(SM_U, U_CP) + c * (U_CP / 8), ka = c * K_CH;
      tab_step<0>(ka, tb, tid); tab_step<1>(ka, tb, tid); tab_step<2>(ka, tb, tid); tab_step<3>(ka, tb, tid);
      bar_sync<4, 128>();
      wg_wait<1>(); conv_load<0>(A0, pa); wg_wait<0>();
      pin(acc);
      conv_load<6>(A1, pa);
      if (c) {
        PT(6, 49 + 3 * c);
#pragma unroll
        for (int i = 0; i < 14; i++) { acc[4 * i] += acc[4 * i + 10]; acc[4 * i + 1] += acc[4 * i + 11]; }
#pragma unroll
        for (int i = 0; i < 8; i++) {
          float y[2];
#pragma unroll
          for (int e = 0; e < 2; e++) {
            const float snd = hl ? acc[4 * (1 + i) + e] : acc[4 * (8 + i) + e];
            const float own = hl ? (i < 7 ? acc[4 * (9 + i < 16 ? 9 + i : 0) + e] : 0.f) : acc[4 * i + e];
            y[e] = own + __shfl_xor_sync(~0u, snd, 16);
          }
          ap[-4096 * TPM * i] = pack2(y[0], y[1]);
        }
        ap += (c & 1) ? 16 : 112;
        PT(6, 50 + 3 * c);
        if (c == 4) break;
      } else mbar_wait(B_UF, 0, n);
      PT(6, 51 + 3 * c);
      conv_mma<0>(acc, A0, db); conv_mma<6>(acc, A1, db);
      wg_wait<1>(); conv_load<7>(A0, pa); conv_mma<7>(acc, A0, db);
      wg_wait<1>(); conv_load<4>(A1, pa); conv_mma<4>(acc, A1, db);
      wg_wait<1>(); conv_load<5>(A0, pa); conv_mma<5>(acc, A0, db);
      wg_wait<1>(); conv_load<2>(A1, pa); conv_mma<2>(acc, A1, db);
      wg_wait<1>(); conv_load<3>(A0, pa); conv_mma<3>(acc, A0, db);
      wg_wait<1>(); conv_load<1>(A1, pa); conv_mma<1>(acc, A1, db);
      bar_sync<4, 128>();
    }
    bar_arrive<13, 160>();
  } else {
    asm volatile("setmaxnreg.dec.sync.aligned.u32 " STR(RP) ";");
    if (w < 2) {
      if (elect()) {
#pragma unroll 1
        for (int s = 0; s < 32; s++) {
          const int hs = s >= 24, sl = hs ? s & 7 : s & 3;
          const uint32_t bar = (hs ? B_XF : B_WF) + 8 * sl;
          mbar_wait(B_WE + 8 * (sl >> hs), hs | (~s >> 2 & 1), n);
          tma2d(SM_W + ((2 * sl + w) * 8192 >> hs), &p.tm[w + 2 * hs], (s >> 3) * 512 + (f * 64 >> hs), ((s + f) & 7) * 64, bar);
          mbar_expect(bar, 8192 >> hs);
        }
#pragma unroll 1
        for (int i = w; i < 30; i += 2) {
          const int sl = i & 7, bytes = i == 28 ? 256 : 16384;
          const uint32_t bar = B_GF + 8 * sl;
          mbar_wait(B_HR + 8 + 8 * ((i + (i > 28 ? 3 : 0)) >> 3), 0, n);
          mbar_wait(B_GE + 8 * sl, (i >> 3) & 1, n);
          bulk_load(SM_X + sl * 16384, g_t + (m * TPM + i + (i > 28 ? f : 0)) * 1024, bytes, bar);
          tma5d(SM_W + sl * 8192, &p.tm[5], f * 64, 2 * i, bar);
          mbar_expect(bar, bytes + 8192);
        }
      }
    } else {
      if (elect()) {
#pragma unroll 1
        for (int k = 0; k < 8; k++) {
          tma2d(SM_X + (2 * k + w - 2) * 8192, &p.tm[4], ((k + f) & 7) * 64, (2 * m + w - 2) * 64, B_XF + 8 * k);
          mbar_expect(B_XF + 8 * k, 8192);
        }
      }
      const bool hg = (uint32_t)(lane - 1) < 4;
      uint32_t* fl = g_flag + (lane * 16 + (hg ? m : ((lane == 0) == (w == 2)) ? cta >> 4 : f)) * 32;
      if (w == 2) {
        bar_arrive<15, 160>();
        const uint32_t target = (ld_acquire(g_flag + (64 + m) * 32) & ~15u) + 16;
        bool pend = lane < 6;
#pragma unroll 1
        do {
          if (pend && (int)(ld_acquire(fl) - target) >= 0) {
            fence_async_glob();
            mbar_arrive(B_HR + 8 * lane);
            pend = false;
            PT(7, 4 + lane + (lane > 3 ? 70 : 0));
          }
        } while (__any_sync(~0u, pend) && --n > 0);
      } else {
        if (elect()) {
          mbar_wait(B_XF + 8 * PFA, 0, n);
          l2_prefetch(p.wg + cta * 7168, 14336);
          l2_prefetch(p.wu + cta * 7168, 14336);
          l2_prefetch(p.wd + cta * 7168, 14336);
        }
#pragma unroll 1
        for (int j = 0; j < 6; j++) {
          __syncwarp();
          bar_sync_r(8 + j, 160);
          if (lane == j) red_release(fl, hg ? 2 : 1);
        }
      }
    }
  }
}

typedef CUresult (*EncFn)(CUtensorMap*, CUtensorMapDataType, cuuint32_t, void*, const cuuint64_t*, const cuuint64_t*, const cuuint32_t*,
                          const cuuint32_t*, CUtensorMapInterleave, CUtensorMapSwizzle, CUtensorMapL2promotion, CUtensorMapFloatOOBfill);

void encode(EncFn fn, CUtensorMap* tm, void* base, int rank, const cuuint64_t* gd, const cuuint64_t* gs, const cuuint32_t* bd,
            CUtensorMapSwizzle sw = CU_TENSOR_MAP_SWIZZLE_128B) {
  const cuuint32_t es[5] = {1, 1, 1, 1, 1};
  fn(tm, CU_TENSOR_MAP_DATA_TYPE_BFLOAT16, rank, base, gd, gs, bd, es, CU_TENSOR_MAP_INTERLEAVE_NONE, sw,
     CU_TENSOR_MAP_L2_PROMOTION_L2_128B, CU_TENSOR_MAP_FLOAT_OOB_FILL_NONE);
}

}

extern "C" void kernel_launch(void* const* d_in, const int* in_sizes, int n_in, void* d_out, int out_size) {
  static EncFn fn = nullptr;
  if (!fn) {
    cudaDriverEntryPointQueryResult qr;
    cudaGetDriverEntryPoint("cuTensorMapEncodeTiled", (void**)&fn, cudaEnableDefault, &qr);
    cudaFuncSetAttribute(fused_kernel, cudaFuncAttributeMaxDynamicSharedMemorySize, SM_TOTAL);
  }
  Params p;
  {
    const cuuint64_t gd[2] = {1792, 512}, gs[1] = {3584};
    const cuuint32_t bd[2] = {64, 64}, b3[2] = {32, 64};
    encode(fn, &p.tm[0], d_in[8], 2, gd, gs, bd);
    encode(fn, &p.tm[1], d_in[9], 2, gd, gs, bd);
    encode(fn, &p.tm[2], d_in[8], 2, gd, gs, b3, CU_TENSOR_MAP_SWIZZLE_64B);
    encode(fn, &p.tm[3], d_in[9], 2, gd, gs, b3, CU_TENSOR_MAP_SWIZZLE_64B);
  }
  {
    const cuuint64_t gd[2] = {512, 2048}, gs[1] = {1024};
    const cuuint32_t bx[2] = {64, 64};
    encode(fn, &p.tm[4], d_in[0], 2, gd, gs, bx);
  }
  {
    const cuuint64_t gd[5] = {512, 2, 4, 4, 56}, gs[4] = {1024, 8192, 2048, 32768};
    const cuuint32_t bd[5] = {64, 2, 4, 4, 2};
    encode(fn, &p.tm[5], d_in[10], 5, gd, gs, bd);
  }
  {
    const cuuint64_t gd[3] = {512, 128, 16}, gs[2] = {16384, 1024};
    const cuuint32_t bd[3] = {64, 8, 16};
    encode(fn, &p.tm[6], d_out, 3, gd, gs, bd);
  }
  p.lar = (const uint2*)d_in[1]; p.aim = (const uint2*)d_in[2]; p.cre = (const uint2*)d_in[3]; p.cim = (const uint2*)d_in[4];
  p.gw = (const uint2*)d_in[11];
  p.ldt = (const __nv_bfloat16*)d_in[5]; p.dskip = (const __nv_bfloat16*)d_in[6];
  p.wg = (const __nv_bfloat16*)d_in[8]; p.wu = (const __nv_bfloat16*)d_in[9]; p.wd = (const __nv_bfloat16*)d_in[10];
  fused_kernel<<<128, 512, SM_TOTAL, cudaStreamPerThread>>>(p);
}
```

```cpp
#include <cuda_runtime.h>
#include <cuda_bf16.h>
#include <cuda.h>
#include <stdint.h>

#define PFA 6
#define LAG 1
#define PMASK 0xFFFF
#define SS 1
#define ROT 0
#define THR 0
#define SLP 100
#define SKT 1
#define STQ "st.relaxed.gpu"
#define LDQ "ld.relaxed.gpu.global"
#define NLL 16
#define CG 0
#define WT 25
#define RG 160
#define RP 32
#define PFE 0
#define GU 1
#define PF0 16
#define PFD 0
#define NQ 4
#define UBN 1
constexpr int GUC = GU, UB = UBN;
#define STR_(x) #x
#define STR(x) STR_(x)
namespace {

constexpr uint32_t SB    = 1024;
constexpr uint32_t SM_X  = SB;
constexpr uint32_t SM_W  = SM_X + 131072;
constexpr uint32_t SM_A  = SM_X + 7 * 16384;
constexpr uint32_t SM_D  = SM_W + 8192;
constexpr uint32_t SM_C  = SM_W + 65536;
constexpr uint32_t SM_KA = SM_C;
constexpr uint32_t SM_KB = SM_C + 16384;
constexpr uint32_t U_CP  = 2176;
constexpr uint32_t SM_U  = SM_C;
constexpr uint32_t SM_T  = SM_U + 8 * U_CP;
constexpr uint32_t K_CH  = 1344;
constexpr uint32_t SM_K  = SM_C + 28672;
constexpr uint32_t SM_GW = SM_K + 4 * K_CH;
constexpr uint32_t SM_OUT = SM_X;
constexpr uint32_t B_WE = SM_GW + 1024, B_GE = B_WE + 32, B_XF = B_GE + 64, B_WF = B_XF + 64, B_GF = B_WF + 32, B_HR = B_GF + 64, B_UF = B_HR + 48;
constexpr uint32_t SM_PROF = B_UF + 16, SM_EP = SM_PROF + 432;
constexpr uint32_t SM_TOTAL = SM_PROF + 448 - SB;
static_assert(SM_TOTAL <= 232448, "smem");

constexpr int TPM = 29;
__device__ uint4    g_t[16 * TPM * 1024];
__device__ uint4    g_a[16 * 512 * 16];
__device__ uint4    g_ut[512 * 272];
__device__ uint32_t g_flag[80 * 32];
#define PT(G, i)
#define PG(i)

template<int TA,int TB,int AN> __device__ __forceinline__ void wgmma_ss_128(float (&d)[AN], uint32_t alo, uint32_t ahi, uint32_t blo, uint32_t bhi, int sc) {
  asm volatile("{\n.reg .pred p;\n.reg .b64 da, db;\nmov.b64 da, {%64, %65};\nmov.b64 db, {%66, %67};\nsetp.ne.b32 p, %68, 0;\n"
   "wgmma.mma_async.sync.aligned.m64n128k16.f32.bf16.bf16 {%0,%1,%2,%3,%4,%5,%6,%7,%8,%9,%10,%11,%12,%13,%14,%15,%16,%17,%18,%19,%20,%21,%22,%23,%24,%25,%26,%27,%28,%29,%30,%31,%32,%33,%34,%35,%36,%37,%38,%39,%40,%41,%42,%43,%44,%45,%46,%47,%48,%49,%50,%51,%52,%53,%54,%55,%56,%57,%58,%59,%60,%61,%62,%63}, da, db, p, 1, 1, %69, %70;\n}\n"
   : "+f"(d[0]),"+f"(d[1]),"+f"(d[2]),"+f"(d[3]),"+f"(d[4]),"+f"(d[5]),"+f"(d[6]),"+f"(d[7]),"+f"(d[8]),"+f"(d[9]),"+f"(d[10]),"+f"(d[11]),"+f"(d[12]),"+f"(d[13]),"+f"(d[14]),"+f"(d[15]),"+f"(d[16]),"+f"(d[17]),"+f"(d[18]),"+f"(d[19]),"+f"(d[20]),"+f"(d[21]),"+f"(d[22]),"+f"(d[23]),"+f"(d[24]),"+f"(d[25]),"+f"(d[26]),"+f"(d[27]),"+f"(d[28]),"+f"(d[29]),"+f"(d[30]),"+f"(d[31]),"+f"(d[32]),"+f"(d[33]),"+f"(d[34]),"+f"(d[35]),"+f"(d[36]),"+f"(d[37]),"+f"(d[38]),"+f"(d[39]),"+f"(d[40]),"+f"(d[41]),"+f"(d[42]),"+f"(d[43]),"+f"(d[44]),"+f"(d[45]),"+f"(d[46]),"+f"(d[47]),"+f"(d[48]),"+f"(d[49]),"+f"(d[50]),"+f"(d[51]),"+f"(d[52]),"+f"(d[53]),"+f"(d[54]),"+f"(d[55]),"+f"(d[56]),"+f"(d[57]),"+f"(d[58]),"+f"(d[59]),"+f"(d[60]),"+f"(d[61]),"+f"(d[62]),"+f"(d[63])
   : "r"(alo), "r"(ahi), "r"(blo), "r"(bhi), "r"(sc), "n"(TA), "n"(TB));
}
template<int TA,int TB,int AN> __device__ __forceinline__ void wgmma_ss_48(float (&d)[AN], uint32_t alo, uint32_t ahi, uint32_t blo, uint32_t bhi, int sc) {
  asm volatile("{\n.reg .pred p;\n.reg .b64 da, db;\nmov.b64 da, {%24, %25};\nmov.b64 db, {%26, %27};\nsetp.ne.b32 p, %28, 0;\n"
   "wgmma.mma_async.sync.aligned.m64n48k16.f32.bf16.bf16 {%0,%1,%2,%3,%4,%5,%6,%7,%8,%9,%10,%11,%12,%13,%14,%15,%16,%17,%18,%19,%20,%21,%22,%23}, da, db, p, 1, 1, %29, %30;\n}\n"
   : "+f"(d[0]),"+f"(d[1]),"+f"(d[2]),"+f"(d[3]),"+f"(d[4]),"+f"(d[5]),"+f"(d[6]),"+f"(d[7]),"+f"(d[8]),"+f"(d[9]),"+f"(d[10]),"+f"(d[11]),"+f"(d[12]),"+f"(d[13]),"+f"(d[14]),"+f"(d[15]),"+f"(d[16]),"+f"(d[17]),"+f"(d[18]),"+f"(d[19]),"+f"(d[20]),"+f"(d[21]),"+f"(d[22]),"+f"(d[23])
   : "r"(alo), "r"(ahi), "r"(blo), "r"(bhi), "r"(sc), "n"(TA), "n"(TB));
}
template<int N> __device__ __forceinline__ void wgmma_rs(float (&d)[64], uint32_t a0, uint32_t a1, uint32_t a2, uint32_t a3, uint32_t blo, uint32_t bhi, int sc);
template<> __device__ __forceinline__ void wgmma_rs<128>(float (&d)[64], uint32_t a0, uint32_t a1, uint32_t a2, uint32_t a3, uint32_t blo, uint32_t bhi, int sc) {
  asm volatile("{\n.reg .pred p;\n.reg .b64 db;\nmov.b64 db, {%68, %69};\nsetp.ne.b32 p, %70, 0;\n"
   "wgmma.mma_async.sync.aligned.m64n128k16.f32.bf16.bf16 {%0,%1,%2,%3,%4,%5,%6,%7,%8,%9,%10,%11,%12,%13,%14,%15,%16,%17,%18,%19,%20,%21,%22,%23,%24,%25,%26,%27,%28,%29,%30,%31,%32,%33,%34,%35,%36,%37,%38,%39,%40,%41,%42,%43,%44,%45,%46,%47,%48,%49,%50,%51,%52,%53,%54,%55,%56,%57,%58,%59,%60,%61,%62,%63}, {%64,%65,%66,%67}, db, p, 1, 1, 0;\n}\n"
   : "+f"(d[0]),"+f"(d[1]),"+f"(d[2]),"+f"(d[3]),"+f"(d[4]),"+f"(d[5]),"+f"(d[6]),"+f"(d[7]),"+f"(d[8]),"+f"(d[9]),"+f"(d[10]),"+f"(d[11]),"+f"(d[12]),"+f"(d[13]),"+f"(d[14]),"+f"(d[15]),"+f"(d[16]),"+f"(d[17]),"+f"(d[18]),"+f"(d[19]),"+f"(d[20]),"+f"(d[21]),"+f"(d[22]),"+f"(d[23]),"+f"(d[24]),"+f"(d[25]),"+f"(d[26]),"+f"(d[27]),"+f"(d[28]),"+f"(d[29]),"+f"(d[30]),"+f"(d[31]),"+f"(d[32]),"+f"(d[33]),"+f"(d[34]),"+f"(d[35]),"+f"(d[36]),"+f"(d[37]),"+f"(d[38]),"+f"(d[39]),"+f"(d[40]),"+f"(d[41]),"+f"(d[42]),"+f"(d[43]),"+f"(d[44]),"+f"(d[45]),"+f"(d[46]),"+f"(d[47]),"+f"(d[48]),"+f"(d[49]),"+f"(d[50]),"+f"(d[51]),"+f"(d[52]),"+f"(d[53]),"+f"(d[54]),"+f"(d[55]),"+f"(d[56]),"+f"(d[57]),"+f"(d[58]),"+f"(d[59]),"+f"(d[60]),"+f"(d[61]),"+f"(d[62]),"+f"(d[63])
   : "r"(a0), "r"(a1), "r"(a2), "r"(a3), "r"(blo), "r"(bhi), "r"(sc));
}
template<> __device__ __forceinline__ void wgmma_rs<96>(float (&d)[64], uint32_t a0, uint32_t a1, uint32_t a2, uint32_t a3, uint32_t blo, uint32_t bhi, int sc) {
  asm volatile("{\n.reg .pred p;\n.reg .b64 db;\nmov.b64 db, {%52, %53};\nsetp.ne.b32 p, %54, 0;\n"
   "wgmma.mma_async.sync.aligned.m64n96k16.f32.bf16.bf16 {%0,%1,%2,%3,%4,%5,%6,%7,%8,%9,%10,%11,%12,%13,%14,%15,%16,%17,%18,%19,%20,%21,%22,%23,%24,%25,%26,%27,%28,%29,%30,%31,%32,%33,%34,%35,%36,%37,%38,%39,%40,%41,%42,%43,%44,%45,%46,%47}, {%48,%49,%50,%51}, db, p, 1, 1, 0;\n}\n"
   : "+f"(d[0]),"+f"(d[1]),"+f"(d[2]),"+f"(d[3]),"+f"(d[4]),"+f"(d[5]),"+f"(d[6]),"+f"(d[7]),"+f"(d[8]),"+f"(d[9]),"+f"(d[10]),"+f"(d[11]),"+f"(d[12]),"+f"(d[13]),"+f"(d[14]),"+f"(d[15]),"+f"(d[16]),"+f"(d[17]),"+f"(d[18]),"+f"(d[19]),"+f"(d[20]),"+f"(d[21]),"+f"(d[22]),"+f"(d[23]),"+f"(d[24]),"+f"(d[25]),"+f"(d[26]),"+f"(d[27]),"+f"(d[28]),"+f"(d[29]),"+f"(d[30]),"+f"(d[31]),"+f"(d[32]),"+f"(d[33]),"+f"(d[34]),"+f"(d[35]),"+f"(d[36]),"+f"(d[37]),"+f"(d[38]),"+f"(d[39]),"+f"(d[40]),"+f"(d[41]),"+f"(d[42]),"+f"(d[43]),"+f"(d[44]),"+f"(d[45]),"+f"(d[46]),"+f"(d[47])
   : "r"(a0), "r"(a1), "r"(a2), "r"(a3), "r"(blo), "r"(bhi), "r"(sc));
}
template<> __device__ __forceinline__ void wgmma_rs<64>(float (&d)[64], uint32_t a0, uint32_t a1, uint32_t a2, uint32_t a3, uint32_t blo, uint32_t bhi, int sc) {
  asm volatile("{\n.reg .pred p;\n.reg .b64 db;\nmov.b64 db, {%36, %37};\nsetp.ne.b32 p, %38, 0;\n"
   "wgmma.mma_async.sync.aligned.m64n64k16.f32.bf16.bf16 {%0,%1,%2,%3,%4,%5,%6,%7,%8,%9,%10,%11,%12,%13,%14,%15,%16,%17,%18,%19,%20,%21,%22,%23,%24,%25,%26,%27,%28,%29,%30,%31}, {%32,%33,%34,%35}, db, p, 1, 1, 0;\n}\n"
   : "+f"(d[0]),"+f"(d[1]),"+f"(d[2]),"+f"(d[3]),"+f"(d[4]),"+f"(d[5]),"+f"(d[6]),"+f"(d[7]),"+f"(d[8]),"+f"(d[9]),"+f"(d[10]),"+f"(d[11]),"+f"(d[12]),"+f"(d[13]),"+f"(d[14]),"+f"(d[15]),"+f"(d[16]),"+f"(d[17]),"+f"(d[18]),"+f"(d[19]),"+f"(d[20]),"+f"(d[21]),"+f"(d[22]),"+f"(d[23]),"+f"(d[24]),"+f"(d[25]),"+f"(d[26]),"+f"(d[27]),"+f"(d[28]),"+f"(d[29]),"+f"(d[30]),"+f"(d[31])
   : "r"(a0), "r"(a1), "r"(a2), "r"(a3), "r"(blo), "r"(bhi), "r"(sc));
}
template<> __device__ __forceinline__ void wgmma_rs<32>(float (&d)[64], uint32_t a0, uint32_t a1, uint32_t a2, uint32_t a3, uint32_t blo, uint32_t bhi, int sc) {
  asm volatile("{\n.reg .pred p;\n.reg .b64 db;\nmov.b64 db, {%20, %21};\nsetp.ne.b32 p, %22, 0;\n"
   "wgmma.mma_async.sync.aligned.m64n32k16.f32.bf16.bf16 {%0,%1,%2,%3,%4,%5,%6,%7,%8,%9,%10,%11,%12,%13,%14,%15}, {%16,%17,%18,%19}, db, p, 1, 1, 0;\n}\n"
   : "+f"(d[0]),"+f"(d[1]),"+f"(d[2]),"+f"(d[3]),"+f"(d[4]),"+f"(d[5]),"+f"(d[6]),"+f"(d[7]),"+f"(d[8]),"+f"(d[9]),"+f"(d[10]),"+f"(d[11]),"+f"(d[12]),"+f"(d[13]),"+f"(d[14]),"+f"(d[15])
   : "r"(a0), "r"(a1), "r"(a2), "r"(a3), "r"(blo), "r"(bhi), "r"(sc));
}
__device__ __forceinline__ void wgmma_rs128z(float (&d)[64], uint32_t a0, uint32_t a1, uint32_t a2, uint32_t a3, uint32_t blo, uint32_t bhi, int sc) {
  asm volatile("{\n.reg .pred p;\n.reg .b64 db;\nmov.b64 db, {%68, %69};\nsetp.ne.b32 p, %70, 0;\n"
   "wgmma.mma_async.sync.aligned.m64n128k16.f32.bf16.bf16 {%0,%1,%2,%3,%4,%5,%6,%7,%8,%9,%10,%11,%12,%13,%14,%15,%16,%17,%18,%19,%20,%21,%22,%23,%24,%25,%26,%27,%28,%29,%30,%31,%32,%33,%34,%35,%36,%37,%38,%39,%40,%41,%42,%43,%44,%45,%46,%47,%48,%49,%50,%51,%52,%53,%54,%55,%56,%57,%58,%59,%60,%61,%62,%63}, {%64,%65,%66,%67}, db, p, 1, 1, 0;\n}\n"
   : "=f"(d[0]),"=f"(d[1]),"=f"(d[2]),"=f"(d[3]),"=f"(d[4]),"=f"(d[5]),"=f"(d[6]),"=f"(d[7]),"=f"(d[8]),"=f"(d[9]),"=f"(d[10]),"=f"(d[11]),"=f"(d[12]),"=f"(d[13]),"=f"(d[14]),"=f"(d[15]),"=f"(d[16]),"=f"(d[17]),"=f"(d[18]),"=f"(d[19]),"=f"(d[20]),"=f"(d[21]),"=f"(d[22]),"=f"(d[23]),"=f"(d[24]),"=f"(d[25]),"=f"(d[26]),"=f"(d[27]),"=f"(d[28]),"=f"(d[29]),"=f"(d[30]),"=f"(d[31]),"=f"(d[32]),"=f"(d[33]),"=f"(d[34]),"=f"(d[35]),"=f"(d[36]),"=f"(d[37]),"=f"(d[38]),"=f"(d[39]),"=f"(d[40]),"=f"(d[41]),"=f"(d[42]),"=f"(d[43]),"=f"(d[44]),"=f"(d[45]),"=f"(d[46]),"=f"(d[47]),"=f"(d[48]),"=f"(d[49]),"=f"(d[50]),"=f"(d[51]),"=f"(d[52]),"=f"(d[53]),"=f"(d[54]),"=f"(d[55]),"=f"(d[56]),"=f"(d[57]),"=f"(d[58]),"=f"(d[59]),"=f"(d[60]),"=f"(d[61]),"=f"(d[62]),"=f"(d[63])
   : "r"(a0), "r"(a1), "r"(a2), "r"(a3), "r"(blo), "r"(bhi), "r"(sc));
}
__device__ __forceinline__ void wgmma_rs128t(float (&d)[64], uint32_t a0, uint32_t a1, uint32_t a2, uint32_t a3, uint32_t blo, uint32_t bhi, int sc) {
  asm volatile("{\n.reg .pred p;\n.reg .b64 db;\nmov.b64 db, {%68, %69};\nsetp.ne.b32 p, %70, 0;\n"
   "wgmma.mma_async.sync.aligned.m64n128k16.f32.bf16.bf16 {%0,%1,%2,%3,%4,%5,%6,%7,%8,%9,%10,%11,%12,%13,%14,%15,%16,%17,%18,%19,%20,%21,%22,%23,%24,%25,%26,%27,%28,%29,%30,%31,%32,%33,%34,%35,%36,%37,%38,%39,%40,%41,%42,%43,%44,%45,%46,%47,%48,%49,%50,%51,%52,%53,%54,%55,%56,%57,%58,%59,%60,%61,%62,%63}, {%64,%65,%66,%67}, db, p, 1, 1, 1;\n}\n"
   : "+f"(d[0]),"+f"(d[1]),"+f"(d[2]),"+f"(d[3]),"+f"(d[4]),"+f"(d[5]),"+f"(d[6]),"+f"(d[7]),"+f"(d[8]),"+f"(d[9]),"+f"(d[10]),"+f"(d[11]),"+f"(d[12]),"+f"(d[13]),"+f"(d[14]),"+f"(d[15]),"+f"(d[16]),"+f"(d[17]),"+f"(d[18]),"+f"(d[19]),"+f"(d[20]),"+f"(d[21]),"+f"(d[22]),"+f"(d[23]),"+f"(d[24]),"+f"(d[25]),"+f"(d[26]),"+f"(d[27]),"+f"(d[28]),"+f"(d[29]),"+f"(d[30]),"+f"(d[31]),"+f"(d[32]),"+f"(d[33]),"+f"(d[34]),"+f"(d[35]),"+f"(d[36]),"+f"(d[37]),"+f"(d[38]),"+f"(d[39]),"+f"(d[40]),"+f"(d[41]),"+f"(d[42]),"+f"(d[43]),"+f"(d[44]),"+f"(d[45]),"+f"(d[46]),"+f"(d[47]),"+f"(d[48]),"+f"(d[49]),"+f"(d[50]),"+f"(d[51]),"+f"(d[52]),"+f"(d[53]),"+f"(d[54]),"+f"(d[55]),"+f"(d[56]),"+f"(d[57]),"+f"(d[58]),"+f"(d[59]),"+f"(d[60]),"+f"(d[61]),"+f"(d[62]),"+f"(d[63])
   : "r"(a0), "r"(a1), "r"(a2), "r"(a3), "r"(blo), "r"(bhi), "r"(sc));
}

__device__ __forceinline__ void wg_fence()  { asm volatile("wgmma.fence.sync.aligned;" ::: "memory"); }
__device__ __forceinline__ void wg_commit() { asm volatile("wgmma.commit_group.sync.aligned;" ::: "memory"); }
template<int N> __device__ __forceinline__ void wg_wait() { asm volatile("wgmma.wait_group.sync.aligned %0;" :: "n"(N) : "memory"); }
template<int N> __device__ __forceinline__ void pin(float (&d)[N]) {
#pragma unroll
  for (int i = 0; i < N; i++) asm volatile("" : "+f"(d[i]) :: "memory");
}
__host__ __device__ constexpr uint32_t dlo(uint32_t addr, uint32_t lbo) { return (addr >> 4) | ((lbo >> 4) << 16); }
constexpr uint32_t HI128 = (1024 >> 4) | (1u << 30), HI64 = (512 >> 4) | (2u << 30), HI0 = 128 >> 4;
__device__ __forceinline__ void mbar_init(uint32_t b, int c) { asm volatile("mbarrier.init.shared::cta.b64 [%0], %1;" :: "r"(b), "r"(c) : "memory"); }
__device__ __forceinline__ void mbar_expect(uint32_t b, int bytes) { asm volatile("mbarrier.arrive.expect_tx.shared::cta.b64 _, [%0], %1;" :: "r"(b), "r"(bytes) : "memory"); }
__device__ __forceinline__ void mbar_arrive(uint32_t b) { asm volatile("mbarrier.arrive.shared::cta.b64 _, [%0];" :: "r"(b) : "memory"); }
__device__ __forceinline__ void mbar_wait(uint32_t b, uint32_t par, int& n) {
  asm volatile("{\n.reg .pred p;\nW:\nmbarrier.try_wait.parity.shared::cta.b64 p, [%1], %2;\nadd.s32 %0, %0, -1;\n"
               "setp.gt.and.s32 p, %0, 0, !p;\n@p bra.uni W;\n}" : "+r"(n) : "r"(b), "r"(par) : "memory");
}
__device__ __forceinline__ bool elect() {
  uint32_t r;
  asm volatile("{\n.reg .pred p;\nelect.sync _|p, 0xFFFFFFFF;\nselp.u32 %0, 1, 0, p;\n}" : "=r"(r));
  return r;
}
__device__ __forceinline__ void tma2d(uint32_t dst, const CUtensorMap* tm, int c0, int c1, uint32_t bar) {
  asm volatile("cp.async.bulk.tensor.2d.shared::cluster.global.mbarrier::complete_tx::bytes [%0], [%1, {%2, %3}], [%4];"
               :: "r"(dst), "l"(tm), "r"(c0), "r"(c1), "r"(bar) : "memory");
}
__device__ __forceinline__ void tma5d(uint32_t dst, const CUtensorMap* tm, int c0, int c4, uint32_t bar) {
  asm volatile("cp.async.bulk.tensor.5d.shared::cluster.global.mbarrier::complete_tx::bytes [%0], [%1, {%2, %3, %3, %3, %4}], [%5];"
               :: "r"(dst), "l"(tm), "r"(c0), "r"(0), "r"(c4), "r"(bar) : "memory");
}
__device__ __forceinline__ void bulk_load(uint32_t dst, const void* src, int bytes, uint32_t bar) {
  asm volatile("cp.async.bulk.shared::cluster.global.mbarrier::complete_tx::bytes [%0], [%1], %2, [%3];"
               :: "r"(dst), "l"(src), "r"(bytes), "r"(bar) : "memory");
}
__device__ __forceinline__ void l2_prefetch(const void* src, int bytes) {
  asm volatile("cp.async.bulk.prefetch.L2.global [%0], %1;" :: "l"(src), "r"(bytes) : "memory");
}
__device__ __forceinline__ void tm_prefetch(const CUtensorMap* tm) { asm volatile("prefetch.tensormap [%0];" :: "l"(tm) : "memory"); }
__device__ __forceinline__ void fence_async_smem() { asm volatile("fence.proxy.async.shared::cta;" ::: "memory"); }
__device__ __forceinline__ void fence_async_glob() { asm volatile("fence.proxy.async.global;" ::: "memory"); }
template<int ID, int N> __device__ __forceinline__ void bar_sync()   { asm volatile("bar.sync %0, %1;" :: "n"(ID), "n"(N) : "memory"); }
template<int ID, int N> __device__ __forceinline__ void bar_arrive() { asm volatile("bar.arrive %0, %1;" :: "n"(ID), "n"(N) : "memory"); }
__device__ __forceinline__ void bar_sync_r(int id, int n)   { asm volatile("bar.sync %0, %1;" :: "r"(id), "r"(n) : "memory"); }
__device__ __forceinline__ void bar_arrive_r(int id, int n) { asm volatile("bar.arrive %0, %1;" :: "r"(id), "r"(n) : "memory"); }
__device__ __forceinline__ void red_release(uint32_t* p, uint32_t v) { asm volatile("red.release.gpu.global.add.u32 [%0], %1;" :: "l"(p), "r"(v) : "memory"); }
__device__ __forceinline__ uint32_t ld_acquire(const uint32_t* p) { uint32_t v; asm volatile("ld.acquire.gpu.global.u32 %0, [%1];" : "=r"(v) : "l"(p) : "memory"); return v; }
__device__ __forceinline__ void st_tag(uint32_t* p, uint32_t v) {
  asm volatile(STQ ".global.b32 [%0], %1;" :: "l"(p), "r"(v) : "memory");
}
__device__ __forceinline__ uint4 ld_tag(const uint4* p) {
  uint4 v;
  asm volatile(LDQ ".v4.b32 {%0, %1, %2, %3}, [%4];"
               : "=r"(v.x), "=r"(v.y), "=r"(v.z), "=r"(v.w) : "l"(p) : "memory");
  return v;
}
__device__ __forceinline__ uint32_t ldg16(const void* p) { uint16_t v; asm volatile("ld.global.nc.u16 %0, [%1];" : "=h"(v) : "l"(p)); return v; }
__device__ __forceinline__ uint2 ldg64(const void* p) { uint2 v; asm volatile("ld.global.nc.v2.u32 {%0,%1}, [%2];" : "=r"(v.x), "=r"(v.y) : "l"(p)); return v; }
template<typename T> __device__ __forceinline__ T* fix(T* p) { asm volatile("" : "+l"(p)); return p; }
__device__ __forceinline__ uint32_t lds32(uint32_t a) { uint32_t v; asm volatile("ld.shared.u32 %0, [%1];" : "=r"(v) : "r"(a) : "memory"); return v; }
__device__ __forceinline__ uint32_t lds16(uint32_t a) { uint16_t v; asm volatile("ld.shared.u16 %0, [%1];" : "=h"(v) : "r"(a) : "memory"); return v; }
__device__ __forceinline__ uint4 lds128(uint32_t a) { uint4 v; asm volatile("ld.shared.v4.u32 {%0,%1,%2,%3}, [%4];" : "=r"(v.x), "=r"(v.y), "=r"(v.z), "=r"(v.w) : "r"(a) : "memory"); return v; }
__device__ __forceinline__ void sts16(uint32_t a, uint32_t v) { asm volatile("st.shared.u16 [%0], %1;" :: "r"(a), "h"((uint16_t)v) : "memory"); }
__device__ __forceinline__ void sts32(uint32_t a, uint32_t v) { asm volatile("st.shared.u32 [%0], %1;" :: "r"(a), "r"(v) : "memory"); }
__device__ __forceinline__ void sts128(uint32_t a, uint32_t x, uint32_t y, uint32_t z, uint32_t w) { asm volatile("st.shared.v4.u32 [%0], {%1,%2,%3,%4};" :: "r"(a), "r"(x), "r"(y), "r"(z), "r"(w) : "memory"); }
__device__ __forceinline__ uint32_t pack2(float lo, float hi)      { uint32_t r; asm("cvt.rn.bf16x2.f32 %0, %1, %2;" : "=r"(r) : "f"(hi), "f"(lo)); return r; }
__device__ __forceinline__ uint32_t pack2relu(float lo, float hi)  { uint32_t r; asm("cvt.rn.relu.bf16x2.f32 %0, %1, %2;" : "=r"(r) : "f"(hi), "f"(lo)); return r; }
__device__ __forceinline__ uint32_t mul2(uint32_t a, uint32_t b) { uint32_t r; asm("mul.rn.bf16x2 %0, %1, %2;" : "=r"(r) : "r"(a), "r"(b)); return r; }
__device__ __forceinline__ uint32_t fma2(uint32_t a, uint32_t b, uint32_t c) { uint32_t r; asm("fma.rn.bf16x2 %0, %1, %2, %3;" : "=r"(r) : "r"(a), "r"(b), "r"(c)); return r; }
__device__ __forceinline__ uint32_t sub2(uint32_t a, uint32_t b) { uint32_t r; asm("sub.rn.bf16x2 %0, %1, %2;" : "=r"(r) : "r"(a), "r"(b)); return r; }
__device__ __forceinline__ float bflo(uint32_t v) { return __uint_as_float(v << 16); }
__device__ __forceinline__ float bfhi(uint32_t v) { return __uint_as_float(v & 0xFFFF0000u); }
__device__ __forceinline__ float bfround(float x) { return __uint_as_float(pack2(0.f, x)); }
__device__ __forceinline__ uint32_t pair(uint32_t lo, uint32_t hi) { return __byte_perm(lo, hi, 0x5410); }
__device__ __forceinline__ float ex2(float x) { float r; asm("ex2.approx.ftz.f32 %0, %1;" : "=f"(r) : "f"(x)); return r; }
__device__ __forceinline__ float2 cexp(float al, float om) {
  const float mag = ex2(al);
  return make_float2(mag * __cosf(om), mag * __sinf(om));
}
__device__ __forceinline__ float2 cmul(float2 a, float2 b) {
  return make_float2(fmaf(a.x, b.x, -a.y * b.y), fmaf(a.x, b.y, a.y * b.x));
}

struct Params {
  CUtensorMap tm[5];
  const uint2 *lar, *aim, *cre, *cim, *gw;
  const __nv_bfloat16 *ldt, *dskip, *wg, *wu, *wd;
};

template<int J, int UP, int RH, int N> __device__ __forceinline__ uint4 h_chunk(float (&acc)[N]) {
  uint32_t v[4];
#pragma unroll
  for (int jl = 0; jl < 4; jl++) {
    const int i = 4 * (J + jl) + 2 * RH;
    v[jl] = mul2(pack2relu(acc[i], acc[i + 1]), pack2(acc[UP + i], acc[UP + i + 1]));
  }
  return make_uint4(v[0], v[1], v[2], v[3]);
}
template<int H> __device__ __forceinline__ void conv_load(uint32_t (&A)[16], uint32_t pa) {
#pragma unroll
  for (int jj = 0; jj < 8; jj++) {
    const uint32_t a = pa + 2176 * (H >> 1) + 128 * (4 * (H & 1) + (jj >> 1)) + 16 * (~jj & 1);
    asm volatile("ld.shared.v2.u32 {%0,%1}, [%2];" : "=r"(A[2 * jj]), "=r"(A[2 * jj + 1]) : "r"(a) : "memory");
  }
}
template<int H, int F = 3> __device__ __forceinline__ void conv_mma(float (&acc)[64], uint32_t (&A)[16], uint32_t blo) {
  if (F & 1) wg_fence();
#pragma unroll
  for (int jj = 0; jj < 4; jj++)
    if ((H | jj) == 0) wgmma_rs128z(acc, A[0], A[1], A[2], A[3], blo, HI0, 0); else
    wgmma_rs<128 - 32 * (H >> 1)>(acc, A[4 * jj], A[4 * jj + 1], A[4 * jj + 2], A[4 * jj + 3], blo + 32 * (H >> 1) + 4 * (H & 1) + jj, HI0, 1);
  if (F & 2) wg_commit();
}
struct Tab { uint32_t a0, a1, a2, a3, b0, b2, d0, d2, ta, s1, s2; };
__device__ __forceinline__ void tab_load(uint32_t ka, const Tab& t, uint32_t (&k)[17]) {
  k[0] = lds32(ka + t.a3 - 4); k[1] = lds32(ka + t.a3); k[2] = lds16(ka + t.a0); k[3] = lds16(ka + t.a1); k[4] = lds16(ka + t.a2);
#pragma unroll
  for (int i = 0; i < 6; i++) {
    const uint32_t o = i < 2 ? 128 * i : 128 + 64 * i;
    k[5 + 2 * i] = lds16(ka + (i < 2 ? t.b0 : t.d0) + o); k[6 + 2 * i] = lds16(ka + (i < 2 ? t.b2 : t.d2) + o);
  }
}
__device__ __forceinline__ void tab_store(const Tab& t, int tid, const uint32_t (&k)[17]) {
  uint32_t v[16];
  const uint32_t w0 = tid ? k[0] : 0;
  v[0] = __byte_perm(w0, k[1], 0x3254); v[2] = __byte_perm(w0, k[1], 0x5476); v[1] = pair(k[3], k[2]); v[3] = pair(k[4], k[3]);
#pragma unroll
  for (int i = 0; i < 6; i++) {
    const int j = 4 + 4 * (i >> 1) + (i & 1);
    v[j] = __byte_perm(k[5 + 2 * i], k[6 + 2 * i], i < 2 ? t.s1 : t.s2); v[j + 2] = __byte_perm(k[5 + 2 * i], k[6 + 2 * i], (i < 2 ? t.s1 : t.s2) >> 16);
  }
#pragma unroll
  for (int i = 0; i < 4; i++) sts128(t.ta + 2176 * i, v[4 * i], v[4 * i + 1], v[4 * i + 2], v[4 * i + 3]);
  if (tid >= 120) {
#pragma unroll
    for (int i = 0; i < 4; i++) {
      const uint32_t a = t.ta + 2176 * i - 2048;
      sts32(a, i ? v[4 * i - 3] : 0); sts32(a + 4, v[4 * i]); sts32(a + 8, i ? v[4 * i - 1] : 0); sts32(a + 12, v[4 * i + 2]);
    }
  }
}
__device__ __forceinline__ void sts_re(uint32_t a, const float2 (&v)[8]) { sts128(a, pack2(v[0].x, v[1].x), pack2(v[2].x, v[3].x), pack2(v[4].x, v[5].x), pack2(v[6].x, v[7].x)); }
__device__ __forceinline__ void sts_im(uint32_t a, const float2 (&v)[8]) { sts128(a, pack2(v[0].y, v[1].y), pack2(v[2].y, v[3].y), pack2(v[4].y, v[5].y), pack2(v[6].y, v[7].y)); }
__device__ __forceinline__ uint32_t pack2sel(float a, float b, float c, float d, int s) {
  uint32_t r;
  asm("{\n.reg .pred p;\nsetp.ne.b32 p, %5, 0;\ncvt.rn.bf16x2.f32 %0, %2, %1;\n@p cvt.rn.bf16x2.f32 %0, %4, %3;\n}" : "=&r"(r) : "f"(a), "f"(b), "f"(c), "f"(d), "r"(s));
  return r;
}

__global__ void __launch_bounds__(512, 1) fused_kernel(const __grid_constant__ Params p) {
  const int cta = blockIdx.x, m = cta >> 3, f = cta & 7;
  const int wid = __shfl_sync(~0u, threadIdx.x >> 5, 0);
  const int wgi = wid >> 2, w = wid & 3, tid = threadIdx.x & 127, lane = tid & 31, g = lane >> 2, q = lane & 3;
  int n = 1 << 17;
  PT(0, wgi); PG(110);
  if (wgi != 2) {
    if (wid < 5) tm_prefetch(&p.tm[wid]);
    const uint32_t bb = wgi < 2 ? B_WE + 24 * wid : B_GF + 32 * w;
#pragma unroll
    for (int i = 0; i < 3; i++) mbar_init(bb + 8 * i, max(4 >> wgi, 1));
    if (wgi == 3) mbar_init(bb + 24, 1);
    fence_async_smem();
    bar_sync<0, 384>();
    PT(0, 109);
  }

  if (wgi < 3) {
    constexpr uint32_t dX = dlo(SM_X, 16);
    if (wgi < 2) {
    asm volatile("setmaxnreg.inc.sync.aligned.u32 " STR(RG) ";");
    uint4* h1 = g_t + (m * TPM + f + 8 * wgi) * 1024 + 64 * g + 8 * (3 - w) + (q ^ (3 - w)) + 32;
    if (wgi == 1) {
      const uint2 gw = __ldg(p.gw + ((tid + 16 * (ROT)) & 127));
      g_ut[(128 * f + 8 * m + ((tid >> 3) & 7)) * 136 + 128 + (tid & 7)] = make_uint4(0, 0, 0, 0);
#pragma unroll
      for (int j = 0; j < 8; j++) g_a[cta * 1024 + 128 * j + tid] = make_uint4(~0u, ~0u, ~0u, ~0u);
      uint4* up = g_ut + (64 * f + g) * 272 + (q & 1) * 136 + 127 - (8 * m + 2 * w + (q >> 1));
      const int tl = 32 * w + 16 * ((lane >> 2) & 1) + 4 * (lane >> 3) + (lane & 3);
      const uint32_t la = SM_X + (f - (ROT)) * 16384 + tl * 128 + ((tl & 7) << 4);
      mbar_wait(B_XF + 8 * (f - (ROT)), 0, n);
#pragma unroll
      for (int dg = 0; dg < 8; dg++) {
        uint4 v;
        asm volatile("ldmatrix.sync.aligned.m8n8.x4.trans.shared.b16 {%0,%1,%2,%3}, [%4];"
                     : "=r"(v.x), "=r"(v.y), "=r"(v.z), "=r"(v.w) : "r"(la ^ (dg << 4)) : "memory");
        up[dg * 2176] = v;
      }
      bar_arrive<8, 160>();
      asm volatile("st.shared.v2.u32 [%0], {%1,%2};" :: "r"(SM_GW + 8 * tid), "r"(gw.x), "r"(gw.y) : "memory");
      PT(1, 80);
    }
    uint4* h0 = h1 + 4;
    uint32_t xd = dX;
    {
      constexpr uint32_t dW = dlo(SM_W, 8192);
      float acc0[64], acc1[64];
#pragma unroll 1
      for (int ui = wgi; ui < 4; ui += 2) {
        h0 = fix(h0); h1 = fix(h1);
        if (ui) bar_sync_r(ui, 256);
#pragma unroll 1
        for (int k = 0; k < 8; k++) {
          if (ui == 0) mbar_wait(B_XF + 8 * k, 0, n);
          mbar_wait(B_WF + 8 * (k & 3), k >> 2, n);
          PT(2, (ui < 3 ? 84 + 8 * ui : 70) + k);
          wg_fence();
#pragma unroll
          for (int kk = 0; kk < 4; kk++) wgmma_ss_128<0, 1>(acc0, xd + k * 1024 + kk * 2, HI128, dW + (k & 3) * 1024 + kk * 128, HI128, (k | kk) != 0);
          wg_commit();
          wg_wait<1>();
          if (k > 0 && lane == 0) mbar_arrive(B_WE + 8 * ((k - 1) & 3));
          if (ui < 3) {
            wg_fence();
#pragma unroll
            for (int kk = 0; kk < 4; kk++) wgmma_ss_128<0, 1>(acc1, xd + k * 1024 + 512 + kk * 2, HI128, dW + (k & 3) * 1024 + kk * 128, HI128, (k | kk) != 0);
            wg_commit();
          }
        }
        if (ui < 3) bar_arrive_r(ui + 1, 256);
        wg_wait<0>();
        pin(acc0); pin(acc1);
        if (lane == 0) mbar_arrive(B_WE + 8 * 3);
        PT(3, 8 + ui);
        h0[0]   = h_chunk<0, 32, 0>(acc0); h1[0]   = h_chunk<4, 32, 0>(acc0);
        h0[512] = h_chunk<0, 32, 1>(acc0); h1[512] = h_chunk<4, 32, 1>(acc0);
        if (ui < 3) {
          h1[-32] = h_chunk<0, 32, 0>(acc1); h0[-32] = h_chunk<4, 32, 0>(acc1);
          h1[480] = h_chunk<0, 32, 1>(acc1); h0[480] = h_chunk<4, 32, 1>(acc1);
        }
        bar_arrive_r(9 + ui, 160);
        h0 += 16 * 1024; h1 += 16 * 1024;
        PT(3, 12 + ui);
        if (ui == 1) {
          const int r = 2 * f + (tid >> 6), c = (tid >> 3) & 7;
          const uint32_t xa = SM_X + (16 * (7 - c) + r) * 128 + (((tid ^ r) & 7) << 4), ga = SM_GW + (tid & 7) * 16;
          float s = 0.f;
#pragma unroll GUC
          for (int k = 0; k < 8; k++) {
            const uint4 xv = lds128(xa + k * 16384), gw = lds128(ga + k * 128);
            const uint32_t p0 = mul2(xv.x, gw.x), p1 = mul2(xv.y, gw.y), p2 = mul2(xv.z, gw.z), p3 = mul2(xv.w, gw.w);
            s += ((bflo(p0) + bfhi(p0)) + (bflo(p1) + bfhi(p1))) + ((bflo(p2) + bfhi(p2)) + (bflo(p3) + bfhi(p3)));
          }
          s += __shfl_xor_sync(~0u, s, 1); s += __shfl_xor_sync(~0u, s, 2); s += __shfl_xor_sync(~0u, s, 4);
          const uint32_t gv = pack2(__fdividef(1.f, 1.f + ex2(bfround(s) * -1.4426950408889634f)), 0.f);
          uint16_t* gp = (uint16_t*)(g_t + (m * TPM + 28) * 1024) + (r >> 2) * 32 + (c >> 1) * 8 + (r & 3) * 2 + (c & 1);
          gp[0] = (uint16_t)sub2(0x3F80, gv); gp[128] = (uint16_t)gv;
          const int o = ((f >> 1) - f) * 1024;
          h0 += o - 36 * (f & 1); h1 += o - 28 * (f & 1);
          xd += 512 * (f & 1);
          PT(1, 82);
        }
      }
    }
    if (wgi == 1) mbar_wait(B_UF, 0, n);
    } else {
    const uint2 lar = __ldg(p.lar + cta * 128 + tid), aim = __ldg(p.aim + cta * 128 + tid);
    const uint2 cre = __ldg(p.cre + cta * 128 + tid), cim = __ldg(p.cim + cta * 128 + tid);
    const uint32_t ldt = ldg16(p.ldt + 4 * cta + w), ds0 = ldg16(p.dskip + 4 * cta + (w >> 1)), ds1 = ldg16(p.dskip + 4 * cta + 2 + (w >> 1));
    asm volatile("setmaxnreg.inc.sync.aligned.u32 " STR(RG) ";");
    {
      const float dt = bfround(ex2(bflo(ldt) * 1.4426950408889634f));
      const uint32_t aa = SM_KA + (tid >> 6) * 8192 + (lane >> 3) * 2048 + (w & 1) * 512 + (lane & 7) * 16;
      const uint32_t ba = SM_KB + (tid >> 6) * 6144 + (lane >> 3) * 1536 + (w & 1) * 384 + (lane & 7) * 16;
      float kc0[24], kc1[24];
#pragma unroll 1
      for (int s = 0; s < 4; s++) {
        const uint32_t sel = 0x10 + 0x22 * s;
        const float ar = bfround(ex2(bflo(__byte_perm(lar.x, lar.y, sel)) * 1.4426950408889634f));
        const float al = (ar * dt) * -1.4426950408889634f, om = bflo(__byte_perm(aim.x, aim.y, sel)) * dt;
        float2 v[8], t[8], u[8], z[8];
        v[0] = make_float2(bflo(__byte_perm(cre.x, cre.y, sel)) * (2.f * dt), bflo(__byte_perm(cim.x, cim.y, sel)) * (2.f * dt));
        if (s == 0) PT(5, 48);
        const float2 z1 = cexp(al, om), z64 = cexp(al * 64.f, om * -64.f), z256 = cexp(al * 256.f, om * 256.f);
        z[0] = make_float2(1.f, 0.f); z[1] = cexp(al * 8.f, om * -8.f);
#pragma unroll
        for (int i = 1; i < 8; i++) v[i] = cmul(v[i - 1], z1);
#pragma unroll
        for (int i = 2; i < 8; i++) z[i] = cmul(z[i - 1], z[1]);
#pragma unroll
        for (int i = 0; i < 4; i++) t[i] = cmul(v[2 * i], z256);
        t[4] = cmul(t[0], z256); t[5] = cmul(t[2], z256); t[6] = cmul(t[4], z256); t[7] = cmul(t[5], z256);
        u[0] = cmul(t[6], z256);
#pragma unroll
        for (int i = 1; i < 5; i++) u[i] = cmul(u[i - 1], z256);
        u[5] = u[0]; u[6] = u[1]; u[7] = u[2];
        uint32_t bv[24];
#pragma unroll
        for (int i = 0; i < 4; i++) {
          bv[i]      = pack2(v[2 * i].x, v[2 * i + 1].x); bv[4 + i]  = pack2(t[2 * i].x, t[2 * i + 1].x); bv[8 + i]  = pack2(u[2 * i].x, u[2 * i + 1].x);
          bv[12 + i] = pack2(v[2 * i].y, v[2 * i + 1].y); bv[16 + i] = pack2(t[2 * i].y, t[2 * i + 1].y); bv[20 + i] = pack2(u[2 * i].y, u[2 * i + 1].y);
        }
#pragma unroll
        for (int i = 0; i < 24; i++) asm volatile("" : "+r"(bv[i]));
        asm volatile("" : "+f"(z[7].x), "+f"(z[7].y));
        if (s == SS) PT(8, 63);
        if (s) { wg_wait<0>(); bar_sync<4, 128>(); }
        if (s == SS) PT(8, 68);
#pragma unroll
        for (int i = 0; i < 6; i++) sts128(ba + 128 * i + (i > 2 ? 384 : 0), bv[4 * i], bv[4 * i + 1], bv[4 * i + 2], bv[4 * i + 3]);
#pragma unroll 1
        for (int j = 0;;) {
          sts_re(aa + j, z); sts_im(aa + j + 1024, z);
          j += 128;
          if (j == 512) break;
#pragma unroll
          for (int i = 0; i < 8; i++) {
            const float a = z[i].y * z64.y, b = z[i].x * z64.y;
            z[i].x = fmaf(z[i].x, z64.x, -a); z[i].y = fmaf(z[i].y, z64.x, b);
          }
        }
        if (s == SS) PT(8, 69);
        fence_async_smem();
        if (s == SS) PT(8, 81);
        bar_sync<4, 128>();
        if (s == SS) PT(8, 83);
        wg_fence();
#pragma unroll
        for (int ks = 0; ks < 4; ks++) {
          wgmma_ss_48<1, 1>(kc0, dlo(SM_KA + ks * 2048, 1024), HI0, dlo(SM_KB + ks * 1536, 768), HI0, (s | ks) != 0);
          wgmma_ss_48<1, 1>(kc1, dlo(SM_KA + 8192 + ks * 2048, 1024), HI0, dlo(SM_KB + 6144 + ks * 1536, 768), HI0, (s | ks) != 0);
        }
        wg_commit();
        PT(5, 64 + s);
      }
      const int row = 16 * (w & 1) + g;
      const uint32_t ka = SM_K + (w >> 1) * K_CH;
      const uint32_t k0 = ka + 16 * row + 4 * q, k1 = ka + 512 + (q < 2 ? 8 * row + 4 * q : 128 * q + 4 * row), k1b = k1 + (q < 2 ? 64 : 32);
      const uint32_t k2 = ka + 1024 + 128 * q + 2 * row;
      wg_wait<0>();
      pin(kc0); pin(kc1);
      if ((tid & 63) == 0) { kc0[0] += bflo(ds0); kc0[12] += bflo(ds0); kc1[0] += bflo(ds1); kc1[12] += bflo(ds1); }
#define KOUT(kc, o) _Pragma("unroll") for (int rh = 0; rh < 2; rh++) { \
        sts32(k0 + o + 128 * rh, pack2sel(kc[2 * rh], kc[2 * rh + 1], kc[12 + 2 * rh], kc[13 + 2 * rh], w & 2)); \
        sts32((rh ? k1b : k1) + o, pack2sel(kc[4 + 2 * rh], kc[5 + 2 * rh], kc[16 + 2 * rh], kc[17 + 2 * rh], w & 2)); \
        const uint32_t v = pack2sel(kc[8 + 2 * rh], kc[9 + 2 * rh], kc[20 + 2 * rh], kc[21 + 2 * rh], w & 2); \
        if (q < 3) sts16(k2 + o + 16 * rh, v); \
        if (q < 2) sts16(k2 + o + 64 + 16 * rh, v >> 16); }
      KOUT(kc0, 0)
      KOUT(kc1, 2 * K_CH)
    }
    bar_sync<15, 160>();
    PT(5, 50);
    if (w == 0 && elect()) {
      mbar_wait(B_HR, 0, n);
      bulk_load(SM_U, g_ut + cta * 1088, 8 * U_CP, B_UF);
      mbar_expect(B_UF, 8 * U_CP);
    }
    __syncwarp();
    }
    if (wgi == 0) {
      float acc[64];
      constexpr uint32_t dA = dlo(SM_D, 16);
      int sl = 0, ph = 0;
      uint4 av[8], gv[8];
      const uint4* lp = fix(g_a + (cta * 4 + w) * 256 + lane);
      const uint4* gp = fix(g_t + (m * TPM + 28) * 1024 + q);
#pragma unroll 1
      for (int i = 0; i <= WT; i++) {
        mbar_wait(B_GF + 8 * sl, ph, n);
        PT(4, 20 + i);
        wg_fence();
#pragma unroll
        for (int kk = 0; kk < 4; kk++) wgmma_ss_128<1, 0>(acc, dA + sl * 512 + kk * 128, HI128, dX + sl * 1024 + kk * 2, HI128, (i | kk) != 0);
        wg_commit();
        wg_wait<1>();
        if (i >= LAG && lane == 0) mbar_arrive(B_GE + 8 * (sl < LAG ? sl + 7 - LAG : sl - LAG));
        if (++sl == 7) { sl = 0; ph ^= 1; }
      }
#pragma unroll
      for (int j = 0; j < 8; j++) av[j] = ld_tag(lp + 32 * j);
#pragma unroll
      for (int c = 0; c < 8; c++) gv[c] = ld_tag(gp + 4 * c);
      uint32_t oa = SM_OUT + ((lane >> 4) * 8 + 7 - (lane & 7)) * 128 + (((2 * w + ((lane >> 3) & 1)) ^ (7 - (lane & 7))) << 4);
      asm volatile("" : "+r"(oa));
      bar_sync<13, 128>();
      static_assert(WT >= 24 && WT >= 20 + LAG && WT < 27, "all ring slots are released in the loop above");
#pragma unroll UB
      for (int i = WT - 20; i < 7; i++) {
        mbar_wait(B_GF + 8 * i, 1, n);
        PT(4, 41 + i);
        wg_fence();
#pragma unroll
        for (int kk = 0; kk < 4; kk++) wgmma_ss_128<1, 0>(acc, dA + i * 512 + kk * 128, HI128, dX + i * 1024 + kk * 2, HI128, 1);
        wg_commit();
      }
      PT(4, 17);
#pragma unroll 1
      for (;;) {
        uint32_t s0 = 0, s1 = 0;
#pragma unroll
        for (int j = 0; j < 8; j++) { s0 = __vimax3_u32(s0, av[j].x, av[j].y); s1 = __vimax3_u32(s1, av[j].z, av[j].w); }
#pragma unroll
      for (int c = 0; c < 8; c++) {
        const uint4 gg = gv[4 + (c & 3)];
        av[c].x = mul2(av[c].x, gg.x); av[c].y = mul2(av[c].y, gg.y); av[c].z = mul2(av[c].z, gg.z); av[c].w = mul2(av[c].w, gg.w);
        asm volatile("" : "+r"(av[c].x), "+r"(av[c].y), "+r"(av[c].z), "+r"(av[c].w));
      }
        if (!__any_sync(~0u, max(s0, s1) == ~0u) || --n <= 0) break;
#pragma unroll
        for (int j = 0; j < 8; j++) av[j] = ld_tag(lp + 32 * j);
      }
      PT(4, 16);
      wg_wait<0>();
      pin(acc);
      PT(4, 18);
#pragma unroll
      for (int i2 = 0; i2 < 8; i2++) {
        uint32_t r[4];
#pragma unroll
        for (int e = 0; e < 4; e++) {
          const int i = 2 * i2 + (e >> 1);
          r[e] = fma2(((const uint32_t*)gv)[i], pack2(acc[4 * i + 2 * (e & 1)], acc[4 * i + 2 * (e & 1) + 1]), ((const uint32_t*)av)[16 * (e & 1) + i]);
        }
        asm volatile("stmatrix.sync.aligned.m8n8.x4.trans.shared.b16 [%0], {%1,%2,%3,%4};"
                     :: "r"(oa + i2 * 2048), "r"(r[0]), "r"(r[1]), "r"(r[2]), "r"(r[3]) : "memory");
        if ((i2 + 1) % (8 / NQ) == 0) { fence_async_smem(); bar_arrive_r(i2 / (8 / NQ), 160); }
      }
    } else {
      const bool hl = lane & 16;
      const int cs = wgi == 1 ? 3 : 0, ce = 5 - wgi;
      const uint32_t tbl = wgi == 1 ? SM_A : SM_T;
      uint32_t* ap = fix((uint32_t*)g_a + ((hl ? 7 : 15) * 64 + (cta >> 1)) * 512 + 128 * w + 64 * (cta & 1) + 16 * cs + 4 * q + (g & 3));
      Tab tb;
      tb.b0 = SM_K + 768 + (tid & ~1); tb.b2 = SM_K + 768 + ((tid + 1) & ~1);
      tb.a0 = SM_K + 512 + (tid ? 2 * (tid & ~1) : -2); tb.a1 = SM_K + 512 + 2 * tid; tb.a2 = SM_K + 512 + 2 * ((tid + 1) & ~1); tb.a3 = SM_K + 4 * tid;
      tb.d0 = SM_K + 768 + 2 * ((tid + 1) >> 2); tb.d2 = SM_K + 768 + 2 * ((tid + 2) >> 2);
      tb.ta = tbl + 128 + 16 * tid;
      tb.s1 = tid & 2 ? 0x54541054 : 0x10541010; tb.s2 = tid & 4 ? 0x54541054 : 0x10541010;
      const uint32_t pa = tbl + 8 * (128 * (g >> 2) + 14 + 4 * w + (g & 3) - 4 * q);
      {
      uint32_t A0[16], A1[16], A2[16], A3[16];
      float acc[64];
      wg_fence(); wg_commit();
#pragma unroll 1
      for (int c = cs;; c++) {
        const uint32_t db = dlo(SM_U, U_CP) + c * (U_CP / 8), ka = c * K_CH;
        if (c != ce) {
          uint32_t k[17];
          tab_load(ka, tb, k);
          bar_sync_r(8 - wgi, 128);
          tab_store(tb, tid, k);
          bar_sync_r(8 - wgi, 128);
        }
        wg_wait<1>(); conv_load<0>(A0, pa); wg_wait<0>();
        pin(acc);
        conv_load<6>(A1, pa);
        if (c != cs) {
          PT(6, 49 + 3 * c);
#pragma unroll
          for (int i = 0; i < 14; i++) { acc[4 * i] += acc[4 * i + 10]; acc[4 * i + 1] += acc[4 * i + 11]; }
#pragma unroll
          for (int i = 0; i < 8; i++) {
            float y[2];
#pragma unroll
            for (int e = 0; e < 2; e++) {
              const float snd = hl ? acc[4 * (1 + i) + e] : acc[4 * (8 + i) + e];
              const float own = hl ? (i < 7 ? acc[4 * (9 + i < 16 ? 9 + i : 0) + e] : 0.f) : acc[4 * i + e];
              y[e] = own + __shfl_xor_sync(~0u, snd, 16);
            }
            st_tag(ap - 32768 * i, pack2(y[0], y[1]));
          }
          ap += 16;
          PT(6, 50 + 3 * c);
          if (c == ce) break;
        } else mbar_wait(B_UF, 0, n);
        PT(6, 51 + 3 * c);
#define PC(j) PT(10, (c < 3 ? 84 + 8 * c : 70) + j)
        conv_mma<0>(acc, A0, db); PC(0); conv_mma<6>(acc, A1, db); PC(1);
        wg_wait<1>(); conv_load<7>(A0, pa); conv_mma<7>(acc, A0, db); PC(2);
        wg_wait<1>(); conv_load<4>(A1, pa); conv_mma<4>(acc, A1, db); PC(3);
        wg_wait<1>(); conv_load<5>(A0, pa); conv_mma<5>(acc, A0, db); PC(4);
        wg_wait<1>(); conv_load<2>(A1, pa); conv_mma<2>(acc, A1, db); PC(5);
        wg_wait<1>(); conv_load<3>(A0, pa); conv_mma<3>(acc, A0, db); PC(6);
        wg_wait<1>(); conv_load<1>(A1, pa); conv_mma<1>(acc, A1, db); PC(7);
      }
      }
    }
  } else {
    asm volatile("setmaxnreg.dec.sync.aligned.u32 " STR(RP) ";");
    if (w < 2) {
      if (elect()) {
#pragma unroll 1
        for (int s = 0; s < 32; s++) {
          const int sl = s & 3;
          const uint32_t bar = B_WF + 8 * sl;
          mbar_wait(B_WE + 8 * sl, ~s >> 2 & 1, n);
          tma2d(SM_W + (2 * sl + w) * 8192, &p.tm[w], (s >> 3) * 512 + (s < 24 ? f : f >> 1) * 64, ((s + (ROT)) & 7) * 64, bar);
          mbar_expect(bar, 8192);
        }
        int sl = w, ph = 1;
#pragma unroll 1
        for (int i = w; i < 28; i += 2) {
          constexpr int bytes = 16384;
          const uint32_t bar = B_GF + 8 * sl;
          mbar_wait(B_HR + 8 + 8 * (i >> 3), 0, n);
          mbar_wait(B_WE + 8 * min((i + 1) >> 1, 3), 1, n);
          mbar_wait(B_GE + 8 * sl, ph, n);
          if (i >= 4) PT(9, 80 + i);
          bulk_load(SM_X + sl * 16384, g_t + (m * TPM + i) * 1024, bytes, bar);
          tma5d(SM_D + sl * 8192, &p.tm[3], f * 64, 2 * i, bar);
          mbar_expect(bar, bytes + 8192);
          sl += 2;
          if (sl >= 7) { sl -= 7; ph ^= 1; }
        }
      }
    } else {
      if (elect()) {
#pragma unroll 1
        for (int k = 0; k < 8; k++) {
          tma2d(SM_X + (2 * k + w - 2) * 8192, &p.tm[2], ((k + (ROT)) & 7) * 64, (2 * m + w - 2) * 64, B_XF + 8 * k);
          mbar_expect(B_XF + 8 * k, 8192);
        }
      }
      uint32_t* fl = g_flag + (lane * 16 + (lane ? m : w == 2 ? cta >> 4 : f)) * 32;
      if (w == 2) {
        const uint32_t target = (ld_acquire(g_flag + (64 + m) * 32) & ~15u) + 16;
        bar_arrive<15, 160>();
        bool pend = lane < 5;
#pragma unroll 1
        do {
          if (pend && (int)(ld_acquire(fl) - target) >= 0) {
            fence_async_glob();
            mbar_arrive(B_HR + 8 * lane);
            pend = false;
            PT(7, 4 + lane + (lane > 3 ? 70 : 0));
          }
        } while (__any_sync(~0u, pend) && --n > 0);
      } else {
        if (elect()) {
          mbar_wait(B_XF + 8 * (m >= PF0 ? PFE : PFA), 0, n);
          l2_prefetch(p.wg + cta * 7168, 14336);
          l2_prefetch(p.wu + cta * 7168, 14336);
          if (PFD) mbar_wait(B_XF + 8 * PFD, 0, n);
          l2_prefetch(p.wd + cta * 7168, 14336);
        }
#pragma unroll 1
        for (int j = 0; j < 5; j++) {
          __syncwarp();
          bar_sync_r(8 + j, 160);
          if (lane == j) red_release(fl, lane ? 2 : 1);
        }
#pragma unroll 1
        for (int j = 0; j < NQ; j++) {
          __syncwarp();
          bar_sync_r(j, 160);
          if (lane == 0)
            asm volatile("cp.async.bulk.tensor.3d.global.shared::cta.bulk_group [%0, {%1, %2, %3}], [%4];"
                         :: "l"(&p.tm[4]), "r"(f * 64), "r"(m * 8), "r"(j * (16 / NQ)), "r"(SM_OUT + j * (16384 / NQ)) : "memory");
        }
        asm volatile("cp.async.bulk.commit_group;" ::: "memory");
        asm volatile("cp.async.bulk.wait_group.read 0;" ::: "memory");
        PT(0, 19); PG(111);
      }
    }
  }
}

typedef CUresult (*EncFn)(CUtensorMap*, CUtensorMapDataType, cuuint32_t, void*, const cuuint64_t*, const cuuint64_t*, const cuuint32_t*,
                          const cuuint32_t*, CUtensorMapInterleave, CUtensorMapSwizzle, CUtensorMapL2promotion, CUtensorMapFloatOOBfill);

void encode(EncFn fn, CUtensorMap* tm, void* base, int rank, const cuuint64_t* gd, const cuuint64_t* gs, const cuuint32_t* bd,
            CUtensorMapSwizzle sw = CU_TENSOR_MAP_SWIZZLE_128B) {
  const cuuint32_t es[5] = {1, 1, 1, 1, 1};
  fn(tm, CU_TENSOR_MAP_DATA_TYPE_BFLOAT16, rank, base, gd, gs, bd, es, CU_TENSOR_MAP_INTERLEAVE_NONE, sw,
     CU_TENSOR_MAP_L2_PROMOTION_L2_128B, CU_TENSOR_MAP_FLOAT_OOB_FILL_NONE);
}

}

extern "C" void kernel_launch(void* const* d_in, const int* in_sizes, int n_in, void* d_out, int out_size) {
  static EncFn fn = nullptr;
  if (!fn) {
    cudaDriverEntryPointQueryResult qr;
    cudaGetDriverEntryPoint("cuTensorMapEncodeTiled", (void**)&fn, cudaEnableDefault, &qr);
    cudaFuncSetAttribute(fused_kernel, cudaFuncAttributeMaxDynamicSharedMemorySize, SM_TOTAL);
  }
  Params p;
  {
    const cuuint64_t gd[2] = {1792, 512}, gs[1] = {3584};
    const cuuint32_t bd[2] = {64, 64};
    encode(fn, &p.tm[0], d_in[8], 2, gd, gs, bd);
    encode(fn, &p.tm[1], d_in[9], 2, gd, gs, bd);
  }
  {
    const cuuint64_t gd[2] = {512, 2048}, gs[1] = {1024};
    const cuuint32_t bx[2] = {64, 64};
    encode(fn, &p.tm[2], d_in[0], 2, gd, gs, bx);
  }
  {
    const cuuint64_t gd[5] = {512, 2, 4, 4, 56}, gs[4] = {1024, 8192, 2048, 32768};
    const cuuint32_t bd[5] = {64, 2, 4, 4, 2};
    encode(fn, &p.tm[3], d_in[10], 5, gd, gs, bd);
  }
  {
    const cuuint64_t gd[3] = {512, 128, 16}, gs[2] = {16384, 1024};
    const cuuint32_t bd[3] = {64, 8, 16 / NQ};
    encode(fn, &p.tm[4], d_out, 3, gd, gs, bd);
  }
  p.lar = (const uint2*)d_in[1]; p.aim = (const uint2*)d_in[2]; p.cre = (const uint2*)d_in[3]; p.cim = (const uint2*)d_in[4];
  p.gw = (const uint2*)d_in[11];
  p.ldt = (const __nv_bfloat16*)d_in[5]; p.dskip = (const __nv_bfloat16*)d_in[6];
  p.wg = (const __nv_bfloat16*)d_in[8]; p.wu = (const __nv_bfloat16*)d_in[9]; p.wd = (const __nv_bfloat16*)d_in[10];
  fused_kernel<<<128, 512, SM_TOTAL, cudaStreamPerThread>>>(p);
}
```
